```python
import torch

def _softmax(x, axis=-1):
    return torch.softmax(x, dim=axis)

def _gelu(x):
    return torch.nn.functional.gelu(x, approximate='tanh')

def _silu(x):
    return torch.nn.functional.silu(x)

def _sigmoid(x):
    return torch.sigmoid(x)

def _layernorm(x, axis=-1, eps=1e-05):
    m = x.mean(dim=axis, keepdim=True)
    v = x.var(dim=axis, keepdim=True, unbiased=False)
    return (x - m) / torch.sqrt(v + eps)

def _scatter_add(tgt, idx, src, axis=0):
    return tgt.clone().index_add_(axis, idx, src)

def _segment_sum(src, seg, n):
    out = torch.zeros((n,) + src.shape[1:], dtype=src.dtype)
    return out.index_add_(0, seg, src)

def _pad(x, pw):
    flat = tuple((v for pair in reversed(pw) for v in pair))
    return torch.nn.functional.pad(x, flat)
kernel_name = 'gated_mix__linear_kernel_hedgehog__mixer_gmlp__prompt'

def setup_inputs():

    _w = lambda a: (lambda t: t.to(torch.bfloat16) if t.is_floating_point() else t)(torch.as_tensor(a))

    def _A_setup():
        B, S, D, H = (1, 2048, 448, 16)
        Dh = D // H
        return {'x': _w((lambda *s: torch.randn(*s, dtype=torch.bfloat16) * 0.05)(B, S, D)), 'wqkv': _w((lambda *s: torch.randn(*s, dtype=torch.bfloat16) * 1.6)(D, 3 * D)), 'w_phi': _w((lambda *s: torch.randn(*s, dtype=torch.bfloat16) * 1.6)(H, Dh, Dh) * Dh ** (-0.5)), 'wo': _w((lambda *s: torch.randn(*s, dtype=torch.bfloat16) * 0.1)(D, D))}
    _A_in = _A_setup()

    def _B_setup():
        B, S, D, F = (1, 2048, 448, 1792)
        Fh = F // 2
        return {'x': _w((lambda *s: torch.randn(*s, dtype=torch.bfloat16) * 0.05)(B, S, D)), 'w_in': _w((lambda *s: torch.randn(*s, dtype=torch.bfloat16) * 0.4)(D, 2 * Fh)), 'w_sp': _w(0.01 * (lambda *s: torch.randn(*s, dtype=torch.bfloat16) * 0.4)(S, S)), 'b_sp': _w(1.0 + 0.01 * (lambda *s: torch.randn(*s, dtype=torch.bfloat16) * 0.05)(S)), 'w_out': _w((lambda *s: torch.randn(*s, dtype=torch.bfloat16) * 0.05)(Fh, D))}
    _B_in = _B_setup()
    return {'A_x': _A_in['x'], 'A_wqkv': _A_in['wqkv'], 'A_w_phi': _A_in['w_phi'], 'A_wo': _A_in['wo'], 'B_x': _B_in['x'], 'B_w_in': _B_in['w_in'], 'B_w_sp': _B_in['w_sp'], 'B_b_sp': _B_in['b_sp'], 'B_w_out': _B_in['w_out'], 'gate_w': _w((lambda *s: torch.randn(*s, dtype=torch.bfloat16) * 0.05)(448) * 16.0)}

def reference(A_x, A_wqkv, A_w_phi, A_wo, B_x, B_w_in, B_w_sp, B_b_sp, B_w_out, gate_w):

    def _A_ref(x, wqkv, w_phi, wo):
        B, S, D = x.shape
        H = 16
        Dh = D // H
        qkv = (lambda x, *d: x.permute(*d))((x @ wqkv).reshape(B, S, 3, H, Dh), 2, 0, 3, 1, 4)
        q, k, v = (qkv[0], qkv[1], qkv[2])
        pq = torch.einsum('bhsd,hdf->bhsf', q, w_phi)
        pk = torch.einsum('bhsd,hdf->bhsf', k, w_phi)
        phi_q = torch.concatenate([_softmax(pq, axis=-1), _softmax(-pq, axis=-1)], axis=-1)
        phi_k = torch.concatenate([_softmax(pk, axis=-1), _softmax(-pk, axis=-1)], axis=-1)
        kv = torch.einsum('bhsf,bhsd->bhfd', phi_k, v)
        z = torch.einsum('bhsf->bhf', phi_k)
        num = torch.einsum('bhqf,bhfd->bhqd', phi_q, kv)
        den = torch.einsum('bhqf,bhf->bhq', phi_q, z)[..., None] + 1e-06
        o = num / den
        return (lambda x, *d: x.permute(*d))(o, 0, 2, 1, 3).reshape(B, S, D) @ wo

    def _B_ref(x, w_in, w_sp, b_sp, w_out):
        B, S, D = x.shape
        F = w_in.shape[-1]
        Fh = F // 2
        z = _gelu(torch.einsum('bsd,df->bsf', x, w_in))
        z1 = z[..., :Fh].clone()
        z2 = _layernorm(z[..., Fh:], axis=-1)
        g = torch.einsum('ts,bsf->btf', w_sp, z2) + b_sp[None, :, None]
        return torch.einsum('bsf,fd->bsd', z1 * g, w_out)
    x = A_x
    g = _sigmoid((x * gate_w).sum(-1, keepdims=True))
    a = _A_ref(x, A_wqkv, A_w_phi, A_wo)
    b = _B_ref(x, B_w_in, B_w_sp, B_b_sp, B_w_out)
    return g * a + (1 - g) * b
```

```cpp
#include <cuda_runtime.h>
#include <cuda_bf16.h>
#include <cuda.h>
#include <stdint.h>

namespace hk {

constexpr int SEQ = 2048, DM = 448, FH = 896;
constexpr int NSLOT = 5, SLOT = 32768;
constexpr int OFF_SC = NSLOT * SLOT;
constexpr int OFF_BAR = OFF_SC + 65536;
constexpr int SMEM_BYTES = OFF_BAR + 1024 + 1024;
constexpr int NTHREADS = 640;

constexpr int SC_ZSTG = 0;
constexpr int SC_PHIP = 0;
constexpr int SC_PHIM = 16384;
constexpr int SC_V = 32768;
constexpr int SC_WPHI = 49152;
constexpr int SC_KVB = 0;
constexpr int SC_OSTG = 16384;
constexpr int SC_APART = 0;
constexpr int SC_USTG = 32768;

constexpr int BAR_FULLB = 0, BAR_FULLA = 40, BAR_EMPTY = 80, BAR_ZFREE = 120;
constexpr int OFF_GATE = 256;

struct Params {
  CUtensorMap xb, xa, win, wqkv, wsp, zt, u3, u2, o3, o2, wout, wo, out3;
  const __nv_bfloat16* xa_ptr;
  const __nv_bfloat16* wphi;
  const __nv_bfloat16* bsp;
  const __nv_bfloat16* gatew;
};

__device__ __align__(1024) __nv_bfloat16 g_ZT[FH * SEQ];
__device__ __align__(1024) __nv_bfloat16 g_U[SEQ * FH];
__device__ __align__(1024) __nv_bfloat16 g_O[SEQ * DM];
__device__ __align__(1024) float g_KV[8 * 2 * 56 * 64];
__device__ __align__(1024) float2 g_stats[16 * 128 * 8];
__device__ __align__(1024) float g_gate[SEQ];
__device__ __align__(1024) unsigned g_sync[24 * 32];
#define TSTAMP(role, idx) do { } while (0)

__device__ __forceinline__ uint32_t smem_u32(const void* p) { return (uint32_t)__cvta_generic_to_shared(p); }
__device__ __forceinline__ void mbar_init(uint32_t bar, uint32_t cnt) { asm volatile("mbarrier.init.shared::cta.b64 [%0], %1;" ::"r"(bar), "r"(cnt)); }
__device__ __forceinline__ void mbar_expect_tx(uint32_t bar, uint32_t bytes) { asm volatile("mbarrier.arrive.expect_tx.shared::cta.b64 _, [%0], %1;" ::"r"(bar), "r"(bytes) : "memory"); }
__device__ __forceinline__ void mbar_arrive(uint32_t bar) { asm volatile("mbarrier.arrive.shared::cta.b64 _, [%0];" ::"r"(bar) : "memory"); }
__device__ __forceinline__ bool mbar_try(uint32_t bar, uint32_t parity) {
  uint32_t ok;
  asm volatile("{\n.reg .pred p;\nmbarrier.try_wait.parity.shared::cta.b64 p, [%1], %2;\nselp.u32 %0, 1, 0, p;\n}" : "=r"(ok) : "r"(bar), "r"(parity) : "memory");
  return ok != 0;
}
__device__ __forceinline__ void mbar_wait(uint32_t bar, uint32_t parity) {
  if (mbar_try(bar, parity)) return;
  uint32_t it = 0;
  while (!mbar_try(bar, parity)) { if (++it > (1u << 24)) __trap(); }
}
__device__ __forceinline__ void tma_ld2(uint32_t dst, const CUtensorMap* m, uint32_t bar, int c0, int c1) {
  asm volatile("cp.async.bulk.tensor.2d.shared::cluster.global.mbarrier::complete_tx::bytes [%0], [%1, {%3, %4}], [%2];"
               ::"r"(dst), "l"(m), "r"(bar), "r"(c0), "r"(c1) : "memory");
}
__device__ __forceinline__ void tma_ld3(uint32_t dst, const CUtensorMap* m, uint32_t bar, int c0, int c1, int c2) {
  asm volatile("cp.async.bulk.tensor.3d.shared::cluster.global.mbarrier::complete_tx::bytes [%0], [%1, {%3, %4, %5}], [%2];"
               ::"r"(dst), "l"(m), "r"(bar), "r"(c0), "r"(c1), "r"(c2) : "memory");
}
__device__ __forceinline__ void tma_st2(const CUtensorMap* m, uint32_t src, int c0, int c1) {
  asm volatile("cp.async.bulk.tensor.2d.global.shared::cta.bulk_group [%0, {%2, %3}], [%1];" ::"l"(m), "r"(src), "r"(c0), "r"(c1) : "memory");
}
__device__ __forceinline__ void tma_st3(const CUtensorMap* m, uint32_t src, int c0, int c1, int c2) {
  asm volatile("cp.async.bulk.tensor.3d.global.shared::cta.bulk_group [%0, {%2, %3, %4}], [%1];" ::"l"(m), "r"(src), "r"(c0), "r"(c1), "r"(c2) : "memory");
}
__device__ __forceinline__ void bulk_commit() { asm volatile("cp.async.bulk.commit_group;" ::: "memory"); }
__device__ __forceinline__ void bulk_wait_all() { asm volatile("cp.async.bulk.wait_group 0;" ::: "memory"); }
__device__ __forceinline__ void bulk_wait_read() { asm volatile("cp.async.bulk.wait_group.read 0;" ::: "memory"); }
__device__ __forceinline__ void prefetch_map(const CUtensorMap* m) { asm volatile("prefetch.tensormap [%0];" ::"l"(m) : "memory"); }
__device__ __forceinline__ void fence_async_smem() { asm volatile("fence.proxy.async.shared::cta;" ::: "memory"); }
__device__ __forceinline__ void fence_async_all() { asm volatile("fence.proxy.async;" ::: "memory"); }
__device__ __forceinline__ void bar_sync(int id, int n) { asm volatile("bar.sync %0, %1;" ::"r"(id), "r"(n) : "memory"); }
__device__ __forceinline__ void bar_arrive(int id, int n) { asm volatile("bar.arrive %0, %1;" ::"r"(id), "r"(n) : "memory"); }
__device__ __forceinline__ void wg_fence() { asm volatile("wgmma.fence.sync.aligned;" ::: "memory"); }
__device__ __forceinline__ void wg_commit() { asm volatile("wgmma.commit_group.sync.aligned;" ::: "memory"); }
template <int N> __device__ __forceinline__ void wg_wait() { asm volatile("wgmma.wait_group.sync.aligned %0;" ::"n"(N) : "memory"); }
template <int N> __device__ __forceinline__ void reg_fence(float* d) {
#pragma unroll
  for (int i = 0; i < N; i++) asm volatile("" : "+f"(d[i])::"memory");
}
__device__ __forceinline__ uint64_t desc_k(uint32_t addr) { return (uint64_t)((addr & 0x3FFFF) >> 4) | (1ull << 16) | (64ull << 32) | (1ull << 62); }
__device__ __forceinline__ uint64_t desc_mn(uint32_t addr) { return (uint64_t)((addr & 0x3FFFF) >> 4) | (512ull << 16) | (64ull << 32) | (1ull << 62); }

__device__ __forceinline__ void red_release(unsigned* p) { asm volatile("red.release.gpu.global.add.u32 [%0], 1;" ::"l"(p) : "memory"); }
__device__ __forceinline__ unsigned ld_acquire(const unsigned* p) {
  unsigned v;
  asm volatile("ld.acquire.gpu.global.u32 %0, [%1];" : "=r"(v) : "l"(p) : "memory");
  return v;
}
__device__ __forceinline__ void poll_ge(const unsigned* p, unsigned target) {
  uint32_t it = 0;
  while ((int)(ld_acquire(p) - target) < 0) { if (++it > (1u << 22)) __trap(); }
}
__device__ __forceinline__ uint32_t pack2(float lo, float hi) {
  uint32_t r;
  asm("cvt.rn.bf16x2.f32 %0, %1, %2;" : "=r"(r) : "f"(hi), "f"(lo));
  return r;
}
__device__ __forceinline__ float ex2f(float x) { float y; asm("ex2.approx.ftz.f32 %0, %1;" : "=f"(y) : "f"(x)); return y; }
__device__ __forceinline__ float rcpf(float x) { float y; asm("rcp.approx.ftz.f32 %0, %1;" : "=f"(y) : "f"(x)); return y; }
__device__ __forceinline__ float gelu_f(float x) {
  const float c0 = 0.7978845608028654f, c1 = 0.7978845608028654f * 0.044715f;
  float p = fmaf(x * x, c1, c0);
  float t;
  asm("tanh.approx.f32 %0, %1;" : "=f"(t) : "f"(x * p));
  float h = 0.5f * x;
  return fmaf(h, t, h);
}
__device__ __forceinline__ void stsm4(uint32_t a, uint32_t r0, uint32_t r1, uint32_t r2, uint32_t r3) {
  asm volatile("stmatrix.sync.aligned.m8n8.x4.shared.b16 [%0], {%1, %2, %3, %4};" ::"r"(a), "r"(r0), "r"(r1), "r"(r2), "r"(r3) : "memory");
}
__device__ __forceinline__ void stsm2(uint32_t a, uint32_t r0, uint32_t r1) {
  asm volatile("stmatrix.sync.aligned.m8n8.x2.shared.b16 [%0], {%1, %2};" ::"r"(a), "r"(r0), "r"(r1) : "memory");
}
__device__ __forceinline__ void stsm4t(uint32_t a, uint32_t r0, uint32_t r1, uint32_t r2, uint32_t r3) {
  asm volatile("stmatrix.sync.aligned.m8n8.x4.trans.shared.b16 [%0], {%1, %2, %3, %4};" ::"r"(a), "r"(r0), "r"(r1), "r"(r2), "r"(r3) : "memory");
}
__device__ __forceinline__ float qmax(float v) { v = fmaxf(v, __shfl_xor_sync(~0u, v, 1)); return fmaxf(v, __shfl_xor_sync(~0u, v, 2)); }
__device__ __forceinline__ float qmin(float v) { v = fminf(v, __shfl_xor_sync(~0u, v, 1)); return fminf(v, __shfl_xor_sync(~0u, v, 2)); }
__device__ __forceinline__ float qsum(float v) { v += __shfl_xor_sync(~0u, v, 1); return v + __shfl_xor_sync(~0u, v, 2); }

__device__ __forceinline__ void wgmma_ss_n112_t01(float* d, uint64_t da, uint64_t db, int scale_d) {
  asm volatile("{\n.reg .pred p;\nsetp.ne.b32 p, %58, 0;\n"
    "wgmma.mma_async.sync.aligned.m64n112k16.f32.bf16.bf16 "
    "{%0, %1, %2, %3, %4, %5, %6, %7, %8, %9, %10, %11, %12, %13, %14, %15, %16, %17, %18, %19, %20, %21, %22, %23, %24, %25, %26, %27, %28, %29, %30, %31, %32, %33, %34, %35, %36, %37, %38, %39, %40, %41, %42, %43, %44, %45, %46, %47, %48, %49, %50, %51, %52, %53, %54, %55}, "
    "%56, %57, p, 1, 1, 0, 1;\n}"
    : "+f"(d[0]), "+f"(d[1]), "+f"(d[2]), "+f"(d[3]), "+f"(d[4]), "+f"(d[5]), "+f"(d[6]), "+f"(d[7]), "+f"(d[8]), "+f"(d[9]), "+f"(d[10]), "+f"(d[11]), "+f"(d[12]), "+f"(d[13]), "+f"(d[14]), "+f"(d[15]), "+f"(d[16]), "+f"(d[17]), "+f"(d[18]), "+f"(d[19]), "+f"(d[20]), "+f"(d[21]), "+f"(d[22]), "+f"(d[23]), "+f"(d[24]), "+f"(d[25]), "+f"(d[26]), "+f"(d[27]), "+f"(d[28]), "+f"(d[29]), "+f"(d[30]), "+f"(d[31]), "+f"(d[32]), "+f"(d[33]), "+f"(d[34]), "+f"(d[35]), "+f"(d[36]), "+f"(d[37]), "+f"(d[38]), "+f"(d[39]), "+f"(d[40]), "+f"(d[41]), "+f"(d[42]), "+f"(d[43]), "+f"(d[44]), "+f"(d[45]), "+f"(d[46]), "+f"(d[47]), "+f"(d[48]), "+f"(d[49]), "+f"(d[50]), "+f"(d[51]), "+f"(d[52]), "+f"(d[53]), "+f"(d[54]), "+f"(d[55])
    : "l"(da), "l"(db), "r"(scale_d));
}
__device__ __forceinline__ void wgmma_ss_n112_t00(float* d, uint64_t da, uint64_t db, int scale_d) {
  asm volatile("{\n.reg .pred p;\nsetp.ne.b32 p, %58, 0;\n"
    "wgmma.mma_async.sync.aligned.m64n112k16.f32.bf16.bf16 "
    "{%0, %1, %2, %3, %4, %5, %6, %7, %8, %9, %10, %11, %12, %13, %14, %15, %16, %17, %18, %19, %20, %21, %22, %23, %24, %25, %26, %27, %28, %29, %30, %31, %32, %33, %34, %35, %36, %37, %38, %39, %40, %41, %42, %43, %44, %45, %46, %47, %48, %49, %50, %51, %52, %53, %54, %55}, "
    "%56, %57, p, 1, 1, 0, 0;\n}"
    : "+f"(d[0]), "+f"(d[1]), "+f"(d[2]), "+f"(d[3]), "+f"(d[4]), "+f"(d[5]), "+f"(d[6]), "+f"(d[7]), "+f"(d[8]), "+f"(d[9]), "+f"(d[10]), "+f"(d[11]), "+f"(d[12]), "+f"(d[13]), "+f"(d[14]), "+f"(d[15]), "+f"(d[16]), "+f"(d[17]), "+f"(d[18]), "+f"(d[19]), "+f"(d[20]), "+f"(d[21]), "+f"(d[22]), "+f"(d[23]), "+f"(d[24]), "+f"(d[25]), "+f"(d[26]), "+f"(d[27]), "+f"(d[28]), "+f"(d[29]), "+f"(d[30]), "+f"(d[31]), "+f"(d[32]), "+f"(d[33]), "+f"(d[34]), "+f"(d[35]), "+f"(d[36]), "+f"(d[37]), "+f"(d[38]), "+f"(d[39]), "+f"(d[40]), "+f"(d[41]), "+f"(d[42]), "+f"(d[43]), "+f"(d[44]), "+f"(d[45]), "+f"(d[46]), "+f"(d[47]), "+f"(d[48]), "+f"(d[49]), "+f"(d[50]), "+f"(d[51]), "+f"(d[52]), "+f"(d[53]), "+f"(d[54]), "+f"(d[55])
    : "l"(da), "l"(db), "r"(scale_d));
}
__device__ __forceinline__ void wgmma_ss_n120_t01(float* d, uint64_t da, uint64_t db, int scale_d) {
  asm volatile("{\n.reg .pred p;\nsetp.ne.b32 p, %62, 0;\n"
    "wgmma.mma_async.sync.aligned.m64n120k16.f32.bf16.bf16 "
    "{%0, %1, %2, %3, %4, %5, %6, %7, %8, %9, %10, %11, %12, %13, %14, %15, %16, %17, %18, %19, %20, %21, %22, %23, %24, %25, %26, %27, %28, %29, %30, %31, %32, %33, %34, %35, %36, %37, %38, %39, %40, %41, %42, %43, %44, %45, %46, %47, %48, %49, %50, %51, %52, %53, %54, %55, %56, %57, %58, %59}, "
    "%60, %61, p, 1, 1, 0, 1;\n}"
    : "+f"(d[0]), "+f"(d[1]), "+f"(d[2]), "+f"(d[3]), "+f"(d[4]), "+f"(d[5]), "+f"(d[6]), "+f"(d[7]), "+f"(d[8]), "+f"(d[9]), "+f"(d[10]), "+f"(d[11]), "+f"(d[12]), "+f"(d[13]), "+f"(d[14]), "+f"(d[15]), "+f"(d[16]), "+f"(d[17]), "+f"(d[18]), "+f"(d[19]), "+f"(d[20]), "+f"(d[21]), "+f"(d[22]), "+f"(d[23]), "+f"(d[24]), "+f"(d[25]), "+f"(d[26]), "+f"(d[27]), "+f"(d[28]), "+f"(d[29]), "+f"(d[30]), "+f"(d[31]), "+f"(d[32]), "+f"(d[33]), "+f"(d[34]), "+f"(d[35]), "+f"(d[36]), "+f"(d[37]), "+f"(d[38]), "+f"(d[39]), "+f"(d[40]), "+f"(d[41]), "+f"(d[42]), "+f"(d[43]), "+f"(d[44]), "+f"(d[45]), "+f"(d[46]), "+f"(d[47]), "+f"(d[48]), "+f"(d[49]), "+f"(d[50]), "+f"(d[51]), "+f"(d[52]), "+f"(d[53]), "+f"(d[54]), "+f"(d[55]), "+f"(d[56]), "+f"(d[57]), "+f"(d[58]), "+f"(d[59])
    : "l"(da), "l"(db), "r"(scale_d));
}
__device__ __forceinline__ void wgmma_ss_n56_t01(float* d, uint64_t da, uint64_t db, int scale_d) {
  asm volatile("{\n.reg .pred p;\nsetp.ne.b32 p, %30, 0;\n"
    "wgmma.mma_async.sync.aligned.m64n56k16.f32.bf16.bf16 "
    "{%0, %1, %2, %3, %4, %5, %6, %7, %8, %9, %10, %11, %12, %13, %14, %15, %16, %17, %18, %19, %20, %21, %22, %23, %24, %25, %26, %27}, "
    "%28, %29, p, 1, 1, 0, 1;\n}"
    : "+f"(d[0]), "+f"(d[1]), "+f"(d[2]), "+f"(d[3]), "+f"(d[4]), "+f"(d[5]), "+f"(d[6]), "+f"(d[7]), "+f"(d[8]), "+f"(d[9]), "+f"(d[10]), "+f"(d[11]), "+f"(d[12]), "+f"(d[13]), "+f"(d[14]), "+f"(d[15]), "+f"(d[16]), "+f"(d[17]), "+f"(d[18]), "+f"(d[19]), "+f"(d[20]), "+f"(d[21]), "+f"(d[22]), "+f"(d[23]), "+f"(d[24]), "+f"(d[25]), "+f"(d[26]), "+f"(d[27])
    : "l"(da), "l"(db), "r"(scale_d));
}
__device__ __forceinline__ void wgmma_ss_n64_t11(float* d, uint64_t da, uint64_t db, int scale_d) {
  asm volatile("{\n.reg .pred p;\nsetp.ne.b32 p, %34, 0;\n"
    "wgmma.mma_async.sync.aligned.m64n64k16.f32.bf16.bf16 "
    "{%0, %1, %2, %3, %4, %5, %6, %7, %8, %9, %10, %11, %12, %13, %14, %15, %16, %17, %18, %19, %20, %21, %22, %23, %24, %25, %26, %27, %28, %29, %30, %31}, "
    "%32, %33, p, 1, 1, 1, 1;\n}"
    : "+f"(d[0]), "+f"(d[1]), "+f"(d[2]), "+f"(d[3]), "+f"(d[4]), "+f"(d[5]), "+f"(d[6]), "+f"(d[7]), "+f"(d[8]), "+f"(d[9]), "+f"(d[10]), "+f"(d[11]), "+f"(d[12]), "+f"(d[13]), "+f"(d[14]), "+f"(d[15]), "+f"(d[16]), "+f"(d[17]), "+f"(d[18]), "+f"(d[19]), "+f"(d[20]), "+f"(d[21]), "+f"(d[22]), "+f"(d[23]), "+f"(d[24]), "+f"(d[25]), "+f"(d[26]), "+f"(d[27]), "+f"(d[28]), "+f"(d[29]), "+f"(d[30]), "+f"(d[31])
    : "l"(da), "l"(db), "r"(scale_d));
}
__device__ __forceinline__ void wgmma_rs_n56_t1(float* d, uint32_t a0, uint32_t a1, uint32_t a2, uint32_t a3, uint64_t db, int scale_d) {
  asm volatile("{\n.reg .pred p;\nsetp.ne.b32 p, %33, 0;\n"
    "wgmma.mma_async.sync.aligned.m64n56k16.f32.bf16.bf16 "
    "{%0, %1, %2, %3, %4, %5, %6, %7, %8, %9, %10, %11, %12, %13, %14, %15, %16, %17, %18, %19, %20, %21, %22, %23, %24, %25, %26, %27}, "
    "{%28, %29, %30, %31}, %32, p, 1, 1, 1;\n}"
    : "+f"(d[0]), "+f"(d[1]), "+f"(d[2]), "+f"(d[3]), "+f"(d[4]), "+f"(d[5]), "+f"(d[6]), "+f"(d[7]), "+f"(d[8]), "+f"(d[9]), "+f"(d[10]), "+f"(d[11]), "+f"(d[12]), "+f"(d[13]), "+f"(d[14]), "+f"(d[15]), "+f"(d[16]), "+f"(d[17]), "+f"(d[18]), "+f"(d[19]), "+f"(d[20]), "+f"(d[21]), "+f"(d[22]), "+f"(d[23]), "+f"(d[24]), "+f"(d[25]), "+f"(d[26]), "+f"(d[27])
    : "r"(a0), "r"(a1), "r"(a2), "r"(a3), "l"(db), "r"(scale_d));
}
__device__ __forceinline__ void wgmma_rs_n64_t1(float* d, uint32_t a0, uint32_t a1, uint32_t a2, uint32_t a3, uint64_t db, int scale_d) {
  asm volatile("{\n.reg .pred p;\nsetp.ne.b32 p, %37, 0;\n"
    "wgmma.mma_async.sync.aligned.m64n64k16.f32.bf16.bf16 "
    "{%0, %1, %2, %3, %4, %5, %6, %7, %8, %9, %10, %11, %12, %13, %14, %15, %16, %17, %18, %19, %20, %21, %22, %23, %24, %25, %26, %27, %28, %29, %30, %31}, "
    "{%32, %33, %34, %35}, %36, p, 1, 1, 1;\n}"
    : "+f"(d[0]), "+f"(d[1]), "+f"(d[2]), "+f"(d[3]), "+f"(d[4]), "+f"(d[5]), "+f"(d[6]), "+f"(d[7]), "+f"(d[8]), "+f"(d[9]), "+f"(d[10]), "+f"(d[11]), "+f"(d[12]), "+f"(d[13]), "+f"(d[14]), "+f"(d[15]), "+f"(d[16]), "+f"(d[17]), "+f"(d[18]), "+f"(d[19]), "+f"(d[20]), "+f"(d[21]), "+f"(d[22]), "+f"(d[23]), "+f"(d[24]), "+f"(d[25]), "+f"(d[26]), "+f"(d[27]), "+f"(d[28]), "+f"(d[29]), "+f"(d[30]), "+f"(d[31])
    : "r"(a0), "r"(a1), "r"(a2), "r"(a3), "l"(db), "r"(scale_d));
}

template <int KIND, int NST>
__device__ __forceinline__ void consume(float* acc, uint32_t sbase, uint32_t bar_full, uint32_t bar_empty, int& slot, uint32_t& phases, int w, int lane) {
  int prev = 0;
#pragma unroll 1
  for (int s = 0; s < NST; s++) {
    mbar_wait(bar_full + 8 * slot, (phases >> slot) & 1);
    phases ^= 1u << slot;
    uint32_t sa = sbase + slot * SLOT;
    uint64_t da = desc_k(sa + w * 8192);
    uint64_t db = (KIND == 1) ? desc_k(sa + 16384) : desc_mn(sa + 16384);
    wg_fence();
#pragma unroll
    for (int k = 0; k < 4; k++) {
      int sc = (s | k) != 0;
      if (KIND == 0) wgmma_ss_n112_t01(acc, da + 2 * k, db + 128 * k, sc);
      if (KIND == 1) wgmma_ss_n112_t00(acc, da + 2 * k, db + 2 * k, sc);
      if (KIND == 2) wgmma_ss_n120_t01(acc, da + 2 * k, db + 128 * k, sc);
      if (KIND == 3) wgmma_ss_n56_t01(acc, da + 2 * k, db + 128 * k, sc);
    }
    wg_commit();
    if (s > 0) {
      wg_wait<1>();
      if (lane == 0) mbar_arrive(bar_empty + 8 * prev);
    }
    prev = slot;
    slot = (slot == NSLOT - 1) ? 0 : slot + 1;
  }
  wg_wait<0>();
  if (lane == 0) mbar_arrive(bar_empty + 8 * prev);
}
__device__ __forceinline__ int advance(int slot, int n) { return (slot + n) % NSLOT; }

__device__ __forceinline__ void feature_map(const float* p, uint32_t* out, int q) {
  const float L = 1.4426950408889634f;
  const bool lo = q < 2;
  float v[14], nx[14];
#pragma unroll
  for (int b = 0; b < 7; b++) {
    v[2 * b] = p[4 * b]; v[2 * b + 1] = p[4 * b + 1];
    nx[2 * b] = p[4 * b + 2]; nx[2 * b + 1] = p[4 * b + 3];
  }
#pragma unroll 1
  for (int r = 0; r < 2; r++) {
    float mx0 = fmaxf(fmaxf(fmaxf(v[0], v[1]), fmaxf(v[2], v[3])), fmaxf(v[4], v[5]));
    float mn0 = fminf(fminf(fminf(v[0], v[1]), fminf(v[2], v[3])), fminf(v[4], v[5]));
    float mx1 = fmaxf(fmaxf(fmaxf(v[8], v[9]), fmaxf(v[10], v[11])), fmaxf(v[12], v[13]));
    float mn1 = fminf(fminf(fminf(v[8], v[9]), fminf(v[10], v[11])), fminf(v[12], v[13]));
    const float mx3 = fmaxf(v[6], v[7]), mn3 = fminf(v[6], v[7]);
    if (lo) { mx0 = fmaxf(mx0, mx3); mn0 = fminf(mn0, mn3); } else { mx1 = fmaxf(mx1, mx3); mn1 = fminf(mn1, mn3); }
    mx0 = qmax(mx0); mx1 = qmax(mx1); mn0 = qmin(mn0); mn1 = qmin(mn1);
    const float a0 = -mx0 * L, a1 = -mx1 * L, c0 = mn0 * L, c1 = mn1 * L;
    const float a3 = lo ? a0 : a1, c3 = lo ? c0 : c1;
    float ep[14], em[14];
#pragma unroll
    for (int e = 0; e < 14; e++) {
      const float a = e < 6 ? a0 : (e < 8 ? a3 : a1), c = e < 6 ? c0 : (e < 8 ? c3 : c1);
      ep[e] = ex2f(fmaf(v[e], L, a));
      em[e] = ex2f(fmaf(v[e], -L, c));
    }
    float sp0 = ((ep[0] + ep[1]) + (ep[2] + ep[3])) + (ep[4] + ep[5]), sm0 = ((em[0] + em[1]) + (em[2] + em[3])) + (em[4] + em[5]);
    float sp1 = ((ep[8] + ep[9]) + (ep[10] + ep[11])) + (ep[12] + ep[13]), sm1 = ((em[8] + em[9]) + (em[10] + em[11])) + (em[12] + em[13]);
    const float sp3 = ep[6] + ep[7], sm3 = em[6] + em[7];
    if (lo) { sp0 += sp3; sm0 += sm3; } else { sp1 += sp3; sm1 += sm3; }
    const float rp0 = rcpf(qsum(sp0)), rp1 = rcpf(qsum(sp1)), rm0 = rcpf(qsum(sm0)), rm1 = rcpf(qsum(sm1));
    const float rp3 = lo ? rp0 : rp1, rm3 = lo ? rm0 : rm1;
#pragma unroll
    for (int b = 0; b < 7; b++) {
      const float rp = b < 3 ? rp0 : (b == 3 ? rp3 : rp1), rm = b < 3 ? rm0 : (b == 3 ? rm3 : rm1);
      ep[b] = __uint_as_float(pack2(ep[2 * b] * rp, ep[2 * b + 1] * rp));
      em[b] = __uint_as_float(pack2(em[2 * b] * rm, em[2 * b + 1] * rm));
    }
#pragma unroll
    for (int e = 0; e < 14; e++) { v[e] = nx[e]; nx[e] = e < 7 ? ep[e] : em[e - 7]; }
  }
#pragma unroll
  for (int b = 0; b < 7; b++) {
    out[2 * b] = __float_as_uint(v[b]); out[2 * b + 1] = __float_as_uint(nx[b]);
    out[14 + 2 * b] = __float_as_uint(v[7 + b]); out[14 + 2 * b + 1] = __float_as_uint(nx[7 + b]);
  }
}

template <int NB>
__device__ __forceinline__ void store_frag(uint32_t tile, int row0, const uint32_t* p, int lane) {
  const int m = lane >> 3, rr = lane & 7;
  const int row = row0 + 8 * (m & 1) + rr;
  const uint32_t ra = tile + row * 128;
#pragma unroll
  for (int b = 0; b + 1 < NB; b += 2) stsm4(ra + (((b + (m >> 1)) ^ rr) << 4), p[2 * b], p[2 * b + 1], p[2 * b + 2], p[2 * b + 3]);
  if (NB & 1) stsm2(ra + (((NB - 1) ^ rr) << 4), p[2 * (NB - 1)], p[2 * (NB - 1) + 1]);
}

__global__ void __launch_bounds__(NTHREADS, 1) fused_kernel(const __grid_constant__ Params P) {
  extern __shared__ uint8_t smem_raw[];
  const uint32_t sbase = (smem_u32(smem_raw) + 1023) & ~1023u;
  uint8_t* sgen = smem_raw + (sbase - smem_u32(smem_raw));
  const uint32_t sc = sbase + OFF_SC, bars = sbase + OFF_BAR;
  const int warp = threadIdx.x >> 5, lane = threadIdx.x & 31;
  const int bi = blockIdx.x >> 3, bj = blockIdx.x & 7;
  unsigned* syncI = g_sync + bi * 32;
  unsigned* syncJ = g_sync + (16 + bj) * 32;

  if (threadIdx.x == 512) {
    for (int s = 0; s < NSLOT; s++) {
      mbar_init(bars + BAR_FULLB + 8 * s, 1);
      mbar_init(bars + BAR_FULLA + 8 * s, 1);
      mbar_init(bars + BAR_EMPTY + 8 * s, 8);
    }
    mbar_init(bars + BAR_ZFREE, 2);
    asm volatile("fence.mbarrier_init.release.cluster;" ::: "memory");
    prefetch_map(&P.xb); prefetch_map(&P.win); prefetch_map(&P.xa); prefetch_map(&P.wqkv);
  }
  const unsigned epoch = __ldcg(syncI + 8 + bj);
  __syncthreads();

  if (warp >= 16) {
    asm volatile("setmaxnreg.dec.sync.aligned.u32 32;");
    if (warp == 16 && lane == 0) {
      int slot = 0;
      uint32_t eph = 0;
      auto begin = [&](int n, uint32_t full, uint32_t bytes) {
        if (n >= NSLOT) { mbar_wait(bars + BAR_EMPTY + 8 * slot, (eph >> slot) & 1); eph ^= 1u << slot; }
        mbar_expect_tx(bars + full + 8 * slot, bytes);
      };
      auto next = [&]() { slot = (slot == NSLOT - 1) ? 0 : slot + 1; };
      const int t0 = bi * 128;
      int n = 0;
      TSTAMP(2, 16);
      for (int k = 0; k < 7; k++, n++) {
        begin(n, BAR_FULLB, 32768);
        uint32_t sa = sbase + slot * SLOT, fb = bars + BAR_FULLB + 8 * slot;
        tma_ld2(sa, &P.xb, fb, 64 * k, t0);
        tma_ld3(sa + 16384, &P.win, fb, 0, 8 + bj, 64 * k);
        tma_ld3(sa + 24576, &P.win, fb, 64, 8 + bj, 64 * k);
        TSTAMP(2, 17 + k);
        next();
      }
      TSTAMP(2, 0);
      prefetch_map(&P.wsp); prefetch_map(&P.zt);
      for (int k = 0; k < 7; k++, n++) {
        begin(n, BAR_FULLA, 32768);
        uint32_t sa = sbase + slot * SLOT, fb = bars + BAR_FULLA + 8 * slot;
        tma_ld2(sa, &P.xa, fb, 64 * k, t0);
        tma_ld3(sa + 16384, &P.wqkv, fb, 0, 8 + bj, 64 * k);
        tma_ld3(sa + 24576, &P.wqkv, fb, 0, 16 + bj, 64 * k);
        next();
      }
      TSTAMP(2, 1);
      for (int k = 0; k < 7; k++, n++) {
        begin(n, BAR_FULLB, 32768);
        uint32_t sa = sbase + slot * SLOT, fb = bars + BAR_FULLB + 8 * slot;
        tma_ld2(sa, &P.xb, fb, 64 * k, t0);
        tma_ld3(sa + 16384, &P.win, fb, 0, bj, 64 * k);
        tma_ld3(sa + 24576, &P.win, fb, 64, bj, 64 * k);
        next();
      }
      TSTAMP(2, 2);
      for (int k = 0; k < 7; k++, n++) {
        begin(n, BAR_FULLA, 24576);
        uint32_t sa = sbase + slot * SLOT, fb = bars + BAR_FULLA + 8 * slot;
        tma_ld2(sa, &P.xa, fb, 64 * k, t0);
        tma_ld3(sa + 16384, &P.wqkv, fb, 0, bj, 64 * k);
        next();
      }
      TSTAMP(2, 3);
      prefetch_map(&P.o2); prefetch_map(&P.wo); prefetch_map(&P.u2); prefetch_map(&P.wout);
      poll_ge(syncJ + 0, (epoch + 1) * 32);
      fence_async_all();
      TSTAMP(2, 4);
      for (int k = 0; k < 32; k++, n++) {
        begin(n, BAR_FULLB, 16384 + 14336);
        uint32_t sa = sbase + slot * SLOT, fb = bars + BAR_FULLB + 8 * slot;
        tma_ld2(sa, &P.wsp, fb, 64 * k, t0);
        tma_ld2(sa + 16384, &P.zt, fb, 64 * k, 112 * bj);
        next();
      }
      TSTAMP(2, 5);
      poll_ge(syncI + 2, (epoch + 1) * 16);
      fence_async_all();
      TSTAMP(2, 6);
      for (int k = 0; k < 7; k++, n++) {
        begin(n, BAR_FULLA, 24576);
        uint32_t sa = sbase + slot * SLOT, fb = bars + BAR_FULLA + 8 * slot;
        tma_ld2(sa, &P.o2, fb, 64 * k, t0);
        tma_ld3(sa + 16384, &P.wo, fb, 0, bj, 64 * k);
        next();
      }
      TSTAMP(2, 7);
      {
        int sl = slot;
        for (int k = 0; k < NSLOT; k++, n++) {
          begin(n, BAR_FULLB, 24576);
          tma_ld3(sbase + slot * SLOT + 16384, &P.wout, bars + BAR_FULLB + 8 * slot, 0, bj, 64 * k);
          next();
        }
        TSTAMP(2, 8);
        poll_ge(syncI + 3, (epoch + 1) * 16);
        fence_async_all();
        TSTAMP(2, 9);
        for (int k = 0; k < NSLOT; k++) {
          tma_ld2(sbase + sl * SLOT, &P.u2, bars + BAR_FULLB + 8 * sl, 64 * k, t0);
          sl = (sl == NSLOT - 1) ? 0 : sl + 1;
        }
      }
      for (int k = NSLOT; k < 14; k++, n++) {
        begin(n, BAR_FULLB, 24576);
        uint32_t sa = sbase + slot * SLOT, fb = bars + BAR_FULLB + 8 * slot;
        tma_ld2(sa, &P.u2, fb, 64 * k, t0);
        tma_ld3(sa + 16384, &P.wout, fb, 0, bj, 64 * k);
        next();
      }
      TSTAMP(2, 10);
    }
  } else if (warp < 8) {
    asm volatile("setmaxnreg.inc.sync.aligned.u32 112;");
    const int w = warp >> 2, ww = warp & 3, q = lane & 3;
    const int r0 = 64 * w + 16 * ww + (lane >> 2);
    const bool elected = (ww == 0 && lane == 0);
    int slot = 0;
    uint32_t ph = 0;
    float acc[56];
    consume<0, 7>(acc, sbase, bars + BAR_FULLB, bars + BAR_EMPTY, slot, ph, w, lane);
    reg_fence<56>(acc);
    if (threadIdx.x == 0) TSTAMP(0, 0);
    {
      float s0 = 0.f, s1 = 0.f;
#pragma unroll
      for (int b = 0; b < 14; b++) {
        acc[4 * b] = gelu_f(acc[4 * b]); acc[4 * b + 1] = gelu_f(acc[4 * b + 1]);
        acc[4 * b + 2] = gelu_f(acc[4 * b + 2]); acc[4 * b + 3] = gelu_f(acc[4 * b + 3]);
        s0 += acc[4 * b] + acc[4 * b + 1];
        s1 += acc[4 * b + 2] + acc[4 * b + 3];
      }
      const float m0 = qsum(s0) * (1.f / 112.f), m1 = qsum(s1) * (1.f / 112.f);
      float v0 = 0.f, v1 = 0.f;
#pragma unroll
      for (int b = 0; b < 14; b++) {
        float d0 = acc[4 * b] - m0, d1 = acc[4 * b + 1] - m0, d2 = acc[4 * b + 2] - m1, d3 = acc[4 * b + 3] - m1;
        v0 = fmaf(d0, d0, v0); v0 = fmaf(d1, d1, v0);
        v1 = fmaf(d2, d2, v1); v1 = fmaf(d3, d3, v1);
      }
      v0 = qsum(v0); v1 = qsum(v1);
      if (q == 0) {
        g_stats[(bi * 128 + r0) * 8 + bj] = make_float2(m0, v0);
        g_stats[(bi * 128 + r0 + 8) * 8 + bj] = make_float2(m1, v1);
      }
    }
    bar_sync(1 + w, 128);
    if (elected) red_release(syncI + w);
    if (threadIdx.x == 0) TSTAMP(0, 1);
    if (lane == 0) poll_ge(syncI + w, (epoch + 1) * 8);
    __syncwarp();
    if (threadIdx.x == 0) TSTAMP(0, 2);
    {
      const float4 a = __ldcg(reinterpret_cast<const float4*>(g_stats + (bi * 128 + r0) * 8 + 2 * q));
      const float4 c = __ldcg(reinterpret_cast<const float4*>(g_stats + (bi * 128 + r0 + 8) * 8 + 2 * q));
      const float m0 = qsum(a.x + a.z) * 0.125f, m1 = qsum(c.x + c.z) * 0.125f;
      const float e0 = a.x - m0, e1 = a.z - m0, e2 = c.x - m1, e3 = c.z - m1;
      const float v0 = qsum(a.y + a.w + 112.f * (e0 * e0 + e1 * e1)) * (1.f / 896.f);
      const float v1 = qsum(c.y + c.w + 112.f * (e2 * e2 + e3 * e3)) * (1.f / 896.f);
      const float rs0 = rsqrtf(v0 + 1e-5f), rs1 = rsqrtf(v1 + 1e-5f);
      const uint32_t stg = sc + SC_ZSTG + w * 14336;
      const int m = lane >> 3, rr = lane & 7;
      const uint32_t cofs = (uint32_t)(((2 * ww + (m & 1)) ^ rr) << 4);
#pragma unroll
      for (int b = 0; b < 14; b += 2) {
        uint32_t p0 = pack2((acc[4 * b] - m0) * rs0, (acc[4 * b + 1] - m0) * rs0);
        uint32_t p1 = pack2((acc[4 * b + 2] - m1) * rs1, (acc[4 * b + 3] - m1) * rs1);
        uint32_t p2 = pack2((acc[4 * b + 4] - m0) * rs0, (acc[4 * b + 5] - m0) * rs0);
        uint32_t p3 = pack2((acc[4 * b + 6] - m1) * rs1, (acc[4 * b + 7] - m1) * rs1);
        stsm4t(stg + (8 * (b + (m >> 1)) + rr) * 128 + cofs, p0, p1, p2, p3);
      }
      fence_async_smem();
      bar_sync(1 + w, 128);
      if (elected) {
        tma_st2(&P.zt, stg, bi * 128 + 64 * w, 112 * bj);
        bulk_commit();
        bulk_wait_read();
        mbar_arrive(bars + BAR_ZFREE);
        bulk_wait_all();
        red_release(syncJ + 0);
      }
      __syncwarp();
    }
    if (threadIdx.x == 0) TSTAMP(0, 3);
    slot = advance(slot, 7);
    consume<0, 7>(acc, sbase, bars + BAR_FULLB, bars + BAR_EMPTY, slot, ph, w, lane);
    reg_fence<56>(acc);
    if (threadIdx.x == 0) TSTAMP(0, 4);
    uint32_t z1[28];
#pragma unroll
    for (int b = 0; b < 14; b++) {
      z1[2 * b] = pack2(gelu_f(acc[4 * b]), gelu_f(acc[4 * b + 1]));
      z1[2 * b + 1] = pack2(gelu_f(acc[4 * b + 2]), gelu_f(acc[4 * b + 3]));
    }
    const float bs0 = __bfloat162float(P.bsp[bi * 128 + r0]), bs1 = __bfloat162float(P.bsp[bi * 128 + r0 + 8]);
    if (threadIdx.x == 0) TSTAMP(0, 5);
    slot = advance(slot, 7);
    consume<1, 32>(acc, sbase, bars + BAR_FULLB, bars + BAR_EMPTY, slot, ph, w, lane);
    reg_fence<56>(acc);
    if (threadIdx.x == 0) TSTAMP(0, 6);
    {
      uint32_t u[28];
#pragma unroll
      for (int b = 0; b < 14; b++) {
        float a0 = __uint_as_float(z1[2 * b] << 16), a1 = __uint_as_float(z1[2 * b] & 0xffff0000u);
        float a2 = __uint_as_float(z1[2 * b + 1] << 16), a3 = __uint_as_float(z1[2 * b + 1] & 0xffff0000u);
        u[2 * b] = pack2(a0 * (acc[4 * b] + bs0), a1 * (acc[4 * b + 1] + bs0));
        u[2 * b + 1] = pack2(a2 * (acc[4 * b + 2] + bs1), a3 * (acc[4 * b + 3] + bs1));
      }
      store_frag<8>(sc + SC_USTG, 64 * w + 16 * ww, u, lane);
      store_frag<6>(sc + SC_USTG + 16384, 64 * w + 16 * ww, u + 16, lane);
      fence_async_smem();
      bar_sync(1 + w, 128);
      if (elected) {
        tma_st3(&P.u3, sc + SC_USTG + w * 8192, 0, bj, bi * 128 + 64 * w);
        tma_st3(&P.u3, sc + SC_USTG + 16384 + w * 8192, 64, bj, bi * 128 + 64 * w);
        bulk_commit();
        bulk_wait_all();
        red_release(syncI + 3);
      }
      __syncwarp();
    }
    if (threadIdx.x == 0) TSTAMP(0, 7);
    slot = advance(slot, 7);
    {
      float acc[28];
      consume<3, 14>(acc, sbase, bars + BAR_FULLB, bars + BAR_EMPTY, slot, ph, w, lane);
      reg_fence<28>(acc);
      if (threadIdx.x == 0) TSTAMP(0, 8);
      bar_sync(6, 512);
      const float* ap = reinterpret_cast<const float*>(sgen + OFF_SC + SC_APART) + (threadIdx.x & 255);
      const float* gs = reinterpret_cast<const float*>(sgen + OFF_BAR + OFF_GATE);
      const float g0 = 1.f - gs[r0], g1 = 1.f - gs[r0 + 8];
      uint32_t o[14];
#pragma unroll
      for (int b = 0; b < 7; b++) {
        o[2 * b] = pack2(fmaf(acc[4 * b], g0, ap[(4 * b) * 256]), fmaf(acc[4 * b + 1], g0, ap[(4 * b + 1) * 256]));
        o[2 * b + 1] = pack2(fmaf(acc[4 * b + 2], g1, ap[(4 * b + 2) * 256]), fmaf(acc[4 * b + 3], g1, ap[(4 * b + 3) * 256]));
      }
      store_frag<7>(sc + SC_USTG, 64 * w + 16 * ww, o, lane);
      fence_async_smem();
      bar_sync(1 + w, 128);
      if (elected) {
        tma_st3(&P.out3, sc + SC_USTG + w * 8192, 0, bj, bi * 128 + 64 * w);
        bulk_commit();
        bulk_wait_read();
        if (threadIdx.x == 0) syncI[8 + bj] = epoch + 1;
      }
    }
    if (threadIdx.x == 0) TSTAMP(0, 9);
  } else {
    asm volatile("setmaxnreg.inc.sync.aligned.u32 112;");
    const int tid = threadIdx.x - 256;
    const int w = (warp >> 2) & 1, ww = warp & 3, q = lane & 3;
    const int wrow = 64 * w + 16 * ww;
    const int r0 = wrow + (lane >> 2);
    const bool elected = (ww == 0 && lane == 0);
    {
      uint4* wp = reinterpret_cast<uint4*>(sgen + OFF_SC + SC_WPHI);
      wp[tid] = make_uint4(0, 0, 0, 0);
      wp[tid + 256] = make_uint4(0, 0, 0, 0);
      if (tid < 112) reinterpret_cast<float4*>(g_KV + bj * 7168 + bi * 448)[tid] = make_float4(0.f, 0.f, 0.f, 0.f);
      const int grow = bi * 128 + bj * 16 + (tid >> 4), gl = tid & 15;
      float gsum = 0.f;
#pragma unroll
      for (int m = 0; m < 7; m++) {
        const uint2 xv = __ldg(reinterpret_cast<const uint2*>(P.xa_ptr + grow * DM + 64 * m + 4 * gl));
        const uint2 gv = __ldg(reinterpret_cast<const uint2*>(P.gatew + 64 * m + 4 * gl));
        gsum = fmaf(__uint_as_float(xv.x << 16), __uint_as_float(gv.x << 16), gsum);
        gsum = fmaf(__uint_as_float(xv.x & 0xffff0000u), __uint_as_float(gv.x & 0xffff0000u), gsum);
        gsum = fmaf(__uint_as_float(xv.y << 16), __uint_as_float(gv.y << 16), gsum);
        gsum = fmaf(__uint_as_float(xv.y & 0xffff0000u), __uint_as_float(gv.y & 0xffff0000u), gsum);
      }
#pragma unroll
      for (int o = 8; o > 0; o >>= 1) gsum += __shfl_xor_sync(~0u, gsum, o);
      if (gl == 0) g_gate[grow] = 1.f / (1.f + __expf(-gsum));
      bar_sync(5, 256);
      if (tid == 0) red_release(syncJ + 2);
      const __nv_bfloat16* wsrc = P.wphi + bj * 2 * 784;
      __nv_bfloat16* wt = reinterpret_cast<__nv_bfloat16*>(sgen + OFF_SC + SC_WPHI);
      for (int e = tid; e < 2 * 784; e += 256) {
        const int h = e >= 784, rem = e - h * 784, d = rem / 28, f = rem - d * 28;
        const int k = 28 * h + d, n = 28 * h + f;
        wt[k * 64 + ((((n >> 3) ^ (k & 7)) << 3) | (n & 7))] = wsrc[e];
      }
      fence_async_smem();
      bar_sync(5, 256);
    }
    if (tid == 0) TSTAMP(1, 0);
    int slot = advance(0, 7);
    uint32_t ph = 0;
    const uint64_t dWphi = desc_mn(sc + SC_WPHI);
    {
      float acc[60];
      consume<2, 7>(acc, sbase, bars + BAR_FULLA, bars + BAR_EMPTY, slot, ph, w, lane);
      reg_fence<60>(acc);
      if (tid == 0) TSTAMP(1, 1);
      uint32_t vp[16];
#pragma unroll
      for (int b = 0; b < 7; b++) {
        vp[2 * b] = pack2(acc[32 + 4 * b], acc[32 + 4 * b + 1]);
        vp[2 * b + 1] = pack2(acc[32 + 4 * b + 2], acc[32 + 4 * b + 3]);
      }
      vp[14] = vp[15] = (q == 0) ? 0x00003f80u : 0u;
      store_frag<8>(sc + SC_V, wrow, vp, lane);
      uint32_t kp[16];
#pragma unroll
      for (int i = 0; i < 16; i++) kp[i] = pack2(acc[2 * i], acc[2 * i + 1]);
      float pk[28];
      wg_fence();
#pragma unroll
      for (int k = 0; k < 4; k++) wgmma_rs_n56_t1(pk, kp[4 * k], kp[4 * k + 1], kp[4 * k + 2], kp[4 * k + 3], dWphi + 128 * k, k != 0);
      wg_commit();
      wg_wait<0>();
      reg_fence<28>(pk);
      uint32_t f[28];
      feature_map(pk, f, q);
      if (tid == 0) TSTAMP(1, 2);
      mbar_wait(bars + BAR_ZFREE, 0);
      store_frag<7>(sc + SC_PHIP, wrow, f, lane);
      store_frag<7>(sc + SC_PHIM, wrow, f + 14, lane);
      fence_async_smem();
      if (tid == 0) poll_ge(syncJ + 2, (epoch + 1) * 16);
      bar_sync(5, 256);
      if (tid == 0) TSTAMP(1, 3);
      float kv[32];
      const uint64_t dA = desc_mn(sc + (w ? SC_PHIM : SC_PHIP)), dB = desc_mn(sc + SC_V);
      wg_fence();
#pragma unroll
      for (int k = 0; k < 8; k++) wgmma_ss_n64_t11(kv, dA + 128 * k, dB + 128 * k, k != 0);
      wg_commit();
      wg_wait<0>();
      reg_fence<32>(kv);
      float* kvg = g_KV + (bj * 2 + w) * 3584;
#pragma unroll
      for (int r = 0; r < 2; r++) {
        const int c = 16 * ww + (lane >> 2) + 8 * r;
        if (c < 56) {
          const int lo = c >= 28 ? 28 : 0;
#pragma unroll
          for (int b = 0; b < 8; b++) {
            const int n = 8 * b + 2 * q;
            if ((n >= lo && n < lo + 28) || n == 56)
              asm volatile("red.global.add.v2.f32 [%0], {%1, %2};" ::"l"(kvg + c * 64 + n), "f"(kv[4 * b + 2 * r]), "f"(kv[4 * b + 2 * r + 1]) : "memory");
          }
        }
      }
      bar_sync(3 + w, 128);
      if (elected) red_release(syncJ + 1);
    }
    if (tid == 0) TSTAMP(1, 4);
    slot = advance(slot, 7);
    uint32_t fq[28];
    {
      float accq[28];
      consume<3, 7>(accq, sbase, bars + BAR_FULLA, bars + BAR_EMPTY, slot, ph, w, lane);
      reg_fence<28>(accq);
      if (tid == 0) TSTAMP(1, 5);
      uint32_t qp[14];
#pragma unroll
      for (int i = 0; i < 14; i++) qp[i] = pack2(accq[2 * i], accq[2 * i + 1]);
      float pq[28];
      wg_fence();
#pragma unroll
      for (int k = 0; k < 3; k++) wgmma_rs_n56_t1(pq, qp[4 * k], qp[4 * k + 1], qp[4 * k + 2], qp[4 * k + 3], dWphi + 128 * k, k != 0);
      wgmma_rs_n56_t1(pq, qp[12], qp[13], 0u, 0u, dWphi + 128 * 3, 1);
      wg_commit();
      wg_wait<0>();
      reg_fence<28>(pq);
      feature_map(pq, fq, q);
    }
    if (tid == 0) TSTAMP(1, 6);
    if (tid == 0) poll_ge(syncJ + 1, (epoch + 1) * 32);
    bar_sync(5, 256);
    if (tid == 0) TSTAMP(1, 7);
    {
      const float* kvg = g_KV + bj * 7168;
      for (int it = tid; it < 112 * 8; it += 256) {
        const int k = it >> 3, ch = it & 7;
        const int c = k >= 56 ? k - 56 : k;
        const int hc = c >= 28;
        float x[8];
        if (ch < 7) {
          const float4 a = __ldcg(reinterpret_cast<const float4*>(kvg + k * 64 + 8 * ch));
          const float4 b = __ldcg(reinterpret_cast<const float4*>(kvg + k * 64 + 8 * ch + 4));
          x[0] = a.x; x[1] = a.y; x[2] = a.z; x[3] = a.w; x[4] = b.x; x[5] = b.y; x[6] = b.z; x[7] = b.w;
#pragma unroll
          for (int e = 0; e < 8; e++) { const int n = 8 * ch + e; if ((n >= 28) != hc) x[e] = 0.f; }
        } else {
          const float z = __ldcg(kvg + k * 64 + 56);
#pragma unroll
          for (int e = 0; e < 8; e++) x[e] = 0.f;
          if (hc) x[1] = z; else x[0] = z;
        }
        uint4 v = make_uint4(pack2(x[0], x[1]), pack2(x[2], x[3]), pack2(x[4], x[5]), pack2(x[6], x[7]));
        *reinterpret_cast<uint4*>(sgen + OFF_SC + SC_KVB + k * 128 + ((ch ^ (k & 7)) << 4)) = v;
      }
      fence_async_smem();
      bar_sync(5, 256);
      float o[32];
      const uint64_t dB = desc_mn(sc + SC_KVB);
      wg_fence();
#pragma unroll
      for (int k = 0; k < 7; k++) wgmma_rs_n64_t1(o, fq[4 * k], fq[4 * k + 1], fq[4 * k + 2], fq[4 * k + 3], dB + 128 * k, k != 0);
      wg_commit();
      wg_wait<0>();
      reg_fence<32>(o);
      uint32_t op[14];
#pragma unroll
      for (int r = 0; r < 2; r++) {
        const float d0 = __shfl_sync(~0u, o[28 + 2 * r], lane & ~3), d1 = __shfl_sync(~0u, o[29 + 2 * r], lane & ~3);
        const float i0 = rcpf(d0 + 1e-6f), i1 = rcpf(d1 + 1e-6f), i3 = q < 2 ? i0 : i1;
#pragma unroll
        for (int b = 0; b < 7; b++) {
          const float iv = b < 3 ? i0 : (b == 3 ? i3 : i1);
          op[2 * b + r] = pack2(o[4 * b + 2 * r] * iv, o[4 * b + 2 * r + 1] * iv);
        }
      }
      store_frag<7>(sc + SC_OSTG, wrow, op, lane);
      fence_async_smem();
      bar_sync(3 + w, 128);
      if (elected) {
        tma_st3(&P.o3, sc + SC_OSTG + w * 8192, 0, bj, bi * 128 + 64 * w);
        bulk_commit();
        bulk_wait_all();
        red_release(syncI + 2);
      }
      __syncwarp();
    }
    if (tid == 0) TSTAMP(1, 8);
    slot = advance(slot, 32);
    {
      float acc[28];
      consume<3, 7>(acc, sbase, bars + BAR_FULLA, bars + BAR_EMPTY, slot, ph, w, lane);
      reg_fence<28>(acc);
      if (tid == 0) TSTAMP(1, 9);
      if (lane == 0) poll_ge(syncI + 2, (epoch + 1) * 16);
      __syncwarp();
      const float g0 = __ldcg(g_gate + bi * 128 + r0), g1 = __ldcg(g_gate + bi * 128 + r0 + 8);
      bar_sync(5, 256);
      float* ap = reinterpret_cast<float*>(sgen + OFF_SC + SC_APART) + tid;
#pragma unroll
      for (int b = 0; b < 7; b++) {
        ap[(4 * b) * 256] = acc[4 * b] * g0;
        ap[(4 * b + 1) * 256] = acc[4 * b + 1] * g0;
        ap[(4 * b + 2) * 256] = acc[4 * b + 2] * g1;
        ap[(4 * b + 3) * 256] = acc[4 * b + 3] * g1;
      }
      if (q == 0) {
        float* gs = reinterpret_cast<float*>(sgen + OFF_BAR + OFF_GATE);
        gs[r0] = g0; gs[r0 + 8] = g1;
      }
      bar_arrive(6, 512);
    }
    if (tid == 0) TSTAMP(1, 10);
  }
}

typedef CUresult (*EncodeFn)(CUtensorMap*, CUtensorMapDataType, cuuint32_t, void*, const cuuint64_t*, const cuuint64_t*, const cuuint32_t*,
                             const cuuint32_t*, CUtensorMapInterleave, CUtensorMapSwizzle, CUtensorMapL2promotion, CUtensorMapFloatOOBfill);

static void map2(EncodeFn fn, CUtensorMap* m, const void* p, uint64_t rows, uint64_t cols, uint32_t brows, uint32_t bcols) {
  cuuint64_t gd[2] = {cols, rows};
  cuuint64_t gs[1] = {cols * 2};
  cuuint32_t bd[2] = {bcols, brows};
  cuuint32_t es[2] = {1, 1};
  fn(m, CU_TENSOR_MAP_DATA_TYPE_BFLOAT16, 2, const_cast<void*>(p), gd, gs, bd, es, CU_TENSOR_MAP_INTERLEAVE_NONE, CU_TENSOR_MAP_SWIZZLE_128B,
     CU_TENSOR_MAP_L2_PROMOTION_L2_128B, CU_TENSOR_MAP_FLOAT_OOB_FILL_NONE);
}
static void map3(EncodeFn fn, CUtensorMap* m, const void* p, uint64_t rows, uint64_t nseg, uint64_t seg, uint32_t brows) {
  cuuint64_t gd[3] = {seg, nseg, rows};
  cuuint64_t gs[2] = {seg * 2, nseg * seg * 2};
  cuuint32_t bd[3] = {64, 1, brows};
  cuuint32_t es[3] = {1, 1, 1};
  fn(m, CU_TENSOR_MAP_DATA_TYPE_BFLOAT16, 3, const_cast<void*>(p), gd, gs, bd, es, CU_TENSOR_MAP_INTERLEAVE_NONE, CU_TENSOR_MAP_SWIZZLE_128B,
     CU_TENSOR_MAP_L2_PROMOTION_L2_128B, CU_TENSOR_MAP_FLOAT_OOB_FILL_NONE);
}

}

extern "C" void kernel_launch(void* const* d_in, const int* in_sizes, int n_in, void* d_out, int out_size) {
  using namespace hk;
  (void)in_sizes; (void)n_in; (void)out_size;
  static EncodeFn fn = nullptr;
  static void *pZT, *pU, *pO;
  if (!fn) {
    void* p = nullptr;
    cudaDriverEntryPointQueryResult qr;
    cudaGetDriverEntryPoint("cuTensorMapEncodeTiled", &p, cudaEnableDefault, &qr);
    fn = (EncodeFn)p;
    cudaGetSymbolAddress(&pZT, g_ZT);
    cudaGetSymbolAddress(&pU, g_U);
    cudaGetSymbolAddress(&pO, g_O);
    cudaFuncSetAttribute(fused_kernel, cudaFuncAttributeMaxDynamicSharedMemorySize, SMEM_BYTES);
  }
  Params P;
  map2(fn, &P.xa, d_in[0], SEQ, DM, 128, 64);
  map3(fn, &P.wqkv, d_in[1], DM, 24, 56, 64);
  map3(fn, &P.wo, d_in[3], DM, 8, 56, 64);
  map2(fn, &P.xb, d_in[0], SEQ, DM, 128, 64);
  map3(fn, &P.win, d_in[5], DM, 16, 112, 64);
  map2(fn, &P.wsp, d_in[6], SEQ, SEQ, 128, 64);
  map3(fn, &P.wout, d_in[8], FH, 8, 56, 64);
  map2(fn, &P.zt, pZT, FH, SEQ, 112, 64);
  map3(fn, &P.u3, pU, SEQ, 8, 112, 64);
  map2(fn, &P.u2, pU, SEQ, FH, 128, 64);
  map3(fn, &P.o3, pO, SEQ, 8, 56, 64);
  map2(fn, &P.o2, pO, SEQ, DM, 128, 64);
  map3(fn, &P.out3, d_out, SEQ, 8, 56, 64);
  P.xa_ptr = (const __nv_bfloat16*)d_in[0];
  P.wphi = (const __nv_bfloat16*)d_in[2];
  P.bsp = (const __nv_bfloat16*)d_in[7];
  P.gatew = (const __nv_bfloat16*)d_in[9];
  fused_kernel<<<128, NTHREADS, SMEM_BYTES, cudaStreamPerThread>>>(P);
}
```

```cpp
#include <cuda_runtime.h>
#include <cuda_bf16.h>
#include <cuda.h>
#include <stdint.h>

namespace hk {

constexpr int SEQ = 2048, DM = 448, FH = 896;
constexpr int NTHREADS = 640;
constexpr int OFF_X = 0, OFF_W = 7 * 16384, NW = 4, WSLOT = 16384;
constexpr int NSLOT = 5, SLOT = 32768;
constexpr int OFF_SPARE = NSLOT * SLOT;
constexpr int OFF_SC = OFF_W + NW * WSLOT;
constexpr int OFF_BAR = OFF_SC + 49152;
constexpr int SMEM_BYTES = OFF_BAR + 1024 + 1024;

constexpr int SC_WPHI = 0;
constexpr int SC_ZSTG = 8192;
constexpr int SC_KVS = 8192;
constexpr int SC_KVB = 16384;
constexpr int SC_KVF = 32768;
constexpr int SC_OSTG = 32768;
constexpr int SC_U1 = 0;
constexpr int SC_APART = 16384;
constexpr int SC_RELAY = 8192;

constexpr int BAR_XFULL = 0, BAR_WFULLB = 64, BAR_WFULLA = 96, BAR_WEMPTY = 128, BAR_FULLB = 160, BAR_FULLA = 200, BAR_EMPTY = 240;
constexpr int BAR_ZFREE = 280, BAR_ZRDY = 288, BAR_URDY = 304, BAR_ORDY = 320, BAR_KDRDY = 336, BAR_KVF = 352, BAR_SCFREE = 360;
constexpr int BAR_OALL = 368;
constexpr int BAR_XFREE = 376;
constexpr int BAR_USL = 384 + 32;
constexpr int BAR_RELRDY = 384, BAR_RELDONE = 392, BAR_GRDY = 400, BAR_REL2RDY = 408;
constexpr int OFF_GATE = 512;
#define PF1B_AT 6
#define REGS_A 112
#define REGS_B 112
#define STATS_AT 4
#define PF2_MODE 4

struct Params {
  const __nv_bfloat16 *x_ptr, *win_ptr, *wqkv_ptr, *wsp_ptr, *wout_ptr, *wo_ptr, *wphi, *bsp, *gatew;
  __nv_bfloat16* pad_[7];
  CUtensorMap x, win, wq, ost, wsp, zt, ust, uld, old, wout, wo, out;
};

__device__ __align__(1024) __nv_bfloat16 g_ZT[FH * SEQ];
__device__ __align__(1024) __nv_bfloat16 g_U[SEQ * 1024];
__device__ __align__(1024) __nv_bfloat16 g_O[SEQ * 512];
__device__ __align__(1024) __nv_bfloat16 g_Wq[24 * DM * 64];
__device__ __align__(1024) float g_KV[8 * 3584];
__device__ __align__(1024) uint2 g_stats[16 * 8 * 128];
__device__ __align__(1024) float g_gate[SEQ];
__device__ __align__(1024) unsigned g_sync[26 * 32];
__device__ __forceinline__ uint32_t clk32() { uint32_t c; asm volatile("mov.u32 %0, %%clock;" : "=r"(c)); return c; }
#define TSTAMP(role, idx) do { } while (0)
#define TP(off)

__device__ __forceinline__ uint32_t smem_u32(const void* p) { return (uint32_t)__cvta_generic_to_shared(p); }
__device__ __forceinline__ void mbar_init(uint32_t bar, uint32_t cnt) { asm volatile("mbarrier.init.shared::cta.b64 [%0], %1;" ::"r"(bar), "r"(cnt)); }
__device__ __forceinline__ void mbar_expect_tx(uint32_t bar, uint32_t bytes) { asm volatile("mbarrier.arrive.expect_tx.shared::cta.b64 _, [%0], %1;" ::"r"(bar), "r"(bytes) : "memory"); }
__device__ __forceinline__ void mbar_arrive(uint32_t bar) { asm volatile("mbarrier.arrive.shared::cta.b64 _, [%0];" ::"r"(bar) : "memory"); }
__device__ __forceinline__ bool mbar_try(uint32_t bar, uint32_t parity) {
  uint32_t ok;
  asm volatile("{\n.reg .pred p;\nmbarrier.try_wait.parity.shared::cta.b64 p, [%1], %2;\nselp.u32 %0, 1, 0, p;\n}" : "=r"(ok) : "r"(bar), "r"(parity) : "memory");
  return ok != 0;
}
__device__ __forceinline__ void mbar_wait(uint32_t bar, uint32_t parity) {
  asm volatile(
      "{\n.reg .pred p;\n.reg .u32 it;\n"
      "mbarrier.try_wait.parity.shared::cta.b64 p, [%0], %1;\n"
      "@p bra MW_DONE;\n"
      "mov.u32 it, 0;\n"
      "MW_LOOP:\n"
      "mbarrier.try_wait.parity.shared::cta.b64 p, [%0], %1;\n"
      "@p bra MW_DONE;\n"
      "add.u32 it, it, 1;\n"
      "setp.lt.u32 p, it, 1048576;\n"
      "@p bra MW_LOOP;\n"
      "MW_DONE:\n}"
      ::"r"(bar), "r"(parity) : "memory");
}
__device__ __forceinline__ void mbar_wait_u(uint32_t bar, uint32_t parity) {
  asm volatile(
      "{\n.reg .pred p;\n.reg .u32 it;\n"
      "mbarrier.try_wait.parity.shared::cta.b64 p, [%0], %1;\n"
      "@p bra.uni MW_DONE;\n"
      "mov.u32 it, 0;\n"
      "MW_LOOP:\n"
      "mbarrier.try_wait.parity.shared::cta.b64 p, [%0], %1;\n"
      "@p bra.uni MW_DONE;\n"
      "add.u32 it, it, 1;\n"
      "setp.lt.u32 p, it, 1048576;\n"
      "@p bra.uni MW_LOOP;\n"
      "MW_DONE:\n}"
      ::"r"(bar), "r"(parity) : "memory");
}
__device__ __forceinline__ bool elect_one() {
  uint32_t p;
  asm volatile("{\n.reg .pred P;\nelect.sync _|P, 0xffffffff;\nselp.u32 %0, 1, 0, P;\n}" : "=r"(p));
  return p != 0;
}
__device__ __forceinline__ void tma_ld2(uint32_t dst, const CUtensorMap* m, uint32_t bar, int c0, int c1) {
  asm volatile("cp.async.bulk.tensor.2d.shared::cluster.global.mbarrier::complete_tx::bytes [%0], [%1, {%3, %4}], [%2];"
               ::"r"(dst), "l"(m), "r"(bar), "r"(c0), "r"(c1) : "memory");
}
__device__ __forceinline__ void tma_ld3(uint32_t dst, const CUtensorMap* m, uint32_t bar, int c0, int c1, int c2) {
  asm volatile("cp.async.bulk.tensor.3d.shared::cluster.global.mbarrier::complete_tx::bytes [%0], [%1, {%3, %4, %5}], [%2];"
               ::"r"(dst), "l"(m), "r"(bar), "r"(c0), "r"(c1), "r"(c2) : "memory");
}
__device__ __forceinline__ void tma_st2(const CUtensorMap* m, uint32_t src, int c0, int c1) {
  asm volatile("cp.async.bulk.tensor.2d.global.shared::cta.bulk_group [%0, {%2, %3}], [%1];" ::"l"(m), "r"(src), "r"(c0), "r"(c1) : "memory");
}
__device__ __forceinline__ void tma_st3(const CUtensorMap* m, uint32_t src, int c0, int c1, int c2) {
  asm volatile("cp.async.bulk.tensor.3d.global.shared::cta.bulk_group [%0, {%2, %3, %4}], [%1];" ::"l"(m), "r"(src), "r"(c0), "r"(c1), "r"(c2) : "memory");
}
__device__ __forceinline__ void cp_async16(uint32_t dst, const void* src, uint32_t bytes) {
  asm volatile("cp.async.cg.shared.global [%0], [%1], 16, %2;" ::"r"(dst), "l"(src), "r"(bytes) : "memory");
}
__device__ __forceinline__ void cp_async_arrive(uint32_t bar) { asm volatile("cp.async.mbarrier.arrive.noinc.shared::cta.b64 [%0];" ::"r"(bar) : "memory"); }
__device__ __forceinline__ void bulk_commit() { asm volatile("cp.async.bulk.commit_group;" ::: "memory"); }
__device__ __forceinline__ void bulk_wait_all() { asm volatile("cp.async.bulk.wait_group 0;" ::: "memory"); }
__device__ __forceinline__ void bulk_wait_read() { asm volatile("cp.async.bulk.wait_group.read 0;" ::: "memory"); }
__device__ __forceinline__ void prefetch_map(const CUtensorMap* m) { asm volatile("prefetch.tensormap [%0];" ::"l"(m) : "memory"); }
__device__ __forceinline__ void fence_async_smem() { asm volatile("fence.proxy.async.shared::cta;" ::: "memory"); }
__device__ __forceinline__ void fence_async_global() { asm volatile("fence.proxy.async.global;" ::: "memory"); }
__device__ __forceinline__ void bar_sync(int id, int n) { asm volatile("bar.sync %0, %1;" ::"r"(id), "r"(n) : "memory"); }
__device__ __forceinline__ void bar_arrive(int id, int n) { asm volatile("bar.arrive %0, %1;" ::"r"(id), "r"(n) : "memory"); }
__device__ __forceinline__ void wg_fence() { asm volatile("wgmma.fence.sync.aligned;" ::: "memory"); }
__device__ __forceinline__ void wg_commit() { asm volatile("wgmma.commit_group.sync.aligned;" ::: "memory"); }
template <int N> __device__ __forceinline__ void wg_wait() { asm volatile("wgmma.wait_group.sync.aligned %0;" ::"n"(N) : "memory"); }
template <int N> __device__ __forceinline__ void reg_fence(float* d) {
#pragma unroll
  for (int i = 0; i < N; i++) asm volatile("" : "+f"(d[i])::"memory");
}
__device__ __forceinline__ uint64_t desc_k(uint32_t addr) { return (uint64_t)((addr & 0x3FFFF) >> 4) | (1ull << 16) | (64ull << 32) | (1ull << 62); }
__device__ __forceinline__ uint64_t desc_mn(uint32_t addr) { return (uint64_t)((addr & 0x3FFFF) >> 4) | (512ull << 16) | (64ull << 32) | (1ull << 62); }

__device__ __forceinline__ void red_release(unsigned* p) { asm volatile("red.release.gpu.global.add.u32 [%0], 1;" ::"l"(p) : "memory"); }
__device__ __forceinline__ unsigned ld_acquire(const unsigned* p) {
  unsigned v;
  asm volatile("ld.acquire.gpu.global.u32 %0, [%1];" : "=r"(v) : "l"(p) : "memory");
  return v;
}
__device__ __forceinline__ unsigned ld_relaxed(const unsigned* p) {
  unsigned v;
  asm volatile("ld.relaxed.gpu.global.u32 %0, [%1];" : "=r"(v) : "l"(p) : "memory");
  return v;
}
__device__ __forceinline__ void poll_ge(const unsigned* p, unsigned target) {
  uint32_t it = 0;
  while ((int)(ld_acquire(p) - target) < 0) { if (++it > (1u << 20)) break; }
}
__device__ __forceinline__ void red_relaxed(unsigned* p) { asm volatile("red.relaxed.gpu.global.add.u32 [%0], 1;" ::"l"(p) : "memory"); }
__device__ __forceinline__ void bulk_st(void* dst, uint32_t src, uint32_t bytes) {
  asm volatile("cp.async.bulk.global.shared::cta.bulk_group [%0], [%1], %2;" ::"l"(dst), "r"(src), "r"(bytes) : "memory");
}
__device__ __forceinline__ void bulk_reduce_f32(void* dst, uint32_t src, uint32_t bytes) {
  asm volatile("cp.reduce.async.bulk.global.shared::cta.bulk_group.add.f32 [%0], [%1], %2;" ::"l"(dst), "r"(src), "r"(bytes) : "memory");
}
__device__ __forceinline__ unsigned ld_epoch(const unsigned* p) {
  unsigned v;
  asm volatile("ld.global.cg.u32 %0, [%1];" : "=r"(v) : "l"(p));
  return v;
}
__device__ __forceinline__ void l2_prefetch(const void* p, uint32_t bytes) { asm volatile("cp.async.bulk.prefetch.L2.global [%0], %1;" ::"l"(p), "r"(bytes) : "memory"); }
__device__ __forceinline__ void prefetch_l2(const void* p) { asm volatile("prefetch.global.L2 [%0];" ::"l"(p)); }
__device__ __forceinline__ void bulk_ld(uint32_t dst, const void* src, uint32_t bytes, uint32_t bar) {
  asm volatile("cp.async.bulk.shared::cluster.global.mbarrier::complete_tx::bytes [%0], [%1], %2, [%3];" ::"r"(dst), "l"(src), "r"(bytes), "r"(bar) : "memory");
}
__device__ __forceinline__ uint2 ld_relaxed2(const uint2* p) {
  uint2 v;
  asm volatile("ld.relaxed.gpu.global.v2.u32 {%0, %1}, [%2];" : "=r"(v.x), "=r"(v.y) : "l"(p) : "memory");
  return v;
}
__device__ __forceinline__ void st_relaxed2(uint2* p, uint2 v) {
  asm volatile("st.relaxed.gpu.global.v2.u32 [%0], {%1, %2};" ::"l"(p), "r"(v.x), "r"(v.y) : "memory");
}
__device__ __forceinline__ uint4 ld_relaxed4(const uint4* p) {
  uint4 v;
  asm volatile("ld.relaxed.gpu.global.v4.u32 {%0, %1, %2, %3}, [%4];" : "=r"(v.x), "=r"(v.y), "=r"(v.z), "=r"(v.w) : "l"(p) : "memory");
  return v;
}
__device__ __forceinline__ void st_relaxed4(uint4* p, uint4 v) {
  asm volatile("st.relaxed.gpu.global.v4.u32 [%0], {%1, %2, %3, %4};" ::"l"(p), "r"(v.x), "r"(v.y), "r"(v.z), "r"(v.w) : "memory");
}
__device__ __forceinline__ uint32_t pack2(float lo, float hi) {
  uint32_t r;
  asm("cvt.rn.bf16x2.f32 %0, %1, %2;" : "=r"(r) : "f"(hi), "f"(lo));
  return r;
}
__device__ __forceinline__ float ex2f(float x) { float y; asm("ex2.approx.ftz.f32 %0, %1;" : "=f"(y) : "f"(x)); return y; }
__device__ __forceinline__ float rcpf(float x) { float y; asm("rcp.approx.ftz.f32 %0, %1;" : "=f"(y) : "f"(x)); return y; }
__device__ __forceinline__ float gelu2_f(float x) {
  const float c0 = 0.7978845608028654f, c1 = 0.7978845608028654f * 0.044715f;
  float p = fmaf(x * x, c1, c0);
  float t;
  asm("tanh.approx.f32 %0, %1;" : "=f"(t) : "f"(x * p));
  return fmaf(x, t, x);
}
__device__ __forceinline__ uint32_t gelu2_pack(uint32_t p) {
  uint32_t r;
  asm("cvt.rn.bf16x2.f32 %0, %1, %2;" : "=r"(r) : "f"(gelu2_f(__uint_as_float(p & 0xffff0000u))), "f"(gelu2_f(__uint_as_float(p << 16))));
  return r;
}
__device__ __forceinline__ void stsm4(uint32_t a, uint32_t r0, uint32_t r1, uint32_t r2, uint32_t r3) {
  asm volatile("stmatrix.sync.aligned.m8n8.x4.shared.b16 [%0], {%1, %2, %3, %4};" ::"r"(a), "r"(r0), "r"(r1), "r"(r2), "r"(r3) : "memory");
}
__device__ __forceinline__ void stsm2(uint32_t a, uint32_t r0, uint32_t r1) {
  asm volatile("stmatrix.sync.aligned.m8n8.x2.shared.b16 [%0], {%1, %2};" ::"r"(a), "r"(r0), "r"(r1) : "memory");
}
__device__ __forceinline__ void stsm4t(uint32_t a, uint32_t r0, uint32_t r1, uint32_t r2, uint32_t r3) {
  asm volatile("stmatrix.sync.aligned.m8n8.x4.trans.shared.b16 [%0], {%1, %2, %3, %4};" ::"r"(a), "r"(r0), "r"(r1), "r"(r2), "r"(r3) : "memory");
}
__device__ __forceinline__ float qmax(float v) { v = fmaxf(v, __shfl_xor_sync(~0u, v, 1)); return fmaxf(v, __shfl_xor_sync(~0u, v, 2)); }
__device__ __forceinline__ float qmin(float v) { v = fminf(v, __shfl_xor_sync(~0u, v, 1)); return fminf(v, __shfl_xor_sync(~0u, v, 2)); }
__device__ __forceinline__ float qsum(float v) { v += __shfl_xor_sync(~0u, v, 1); return v + __shfl_xor_sync(~0u, v, 2); }

__device__ __forceinline__ void wgmma_ss_n112_t01(float* d, uint64_t da, uint64_t db, int scale_d) {
  asm volatile("{\n.reg .pred p;\nsetp.ne.b32 p, %58, 0;\n"
    "wgmma.mma_async.sync.aligned.m64n112k16.f32.bf16.bf16 "
    "{%0, %1, %2, %3, %4, %5, %6, %7, %8, %9, %10, %11, %12, %13, %14, %15, %16, %17, %18, %19, %20, %21, %22, %23, %24, %25, %26, %27, %28, %29, %30, %31, %32, %33, %34, %35, %36, %37, %38, %39, %40, %41, %42, %43, %44, %45, %46, %47, %48, %49, %50, %51, %52, %53, %54, %55}, "
    "%56, %57, p, 1, 1, 0, 1;\n}"
    : "+f"(d[0]), "+f"(d[1]), "+f"(d[2]), "+f"(d[3]), "+f"(d[4]), "+f"(d[5]), "+f"(d[6]), "+f"(d[7]), "+f"(d[8]), "+f"(d[9]), "+f"(d[10]), "+f"(d[11]), "+f"(d[12]), "+f"(d[13]), "+f"(d[14]), "+f"(d[15]), "+f"(d[16]), "+f"(d[17]), "+f"(d[18]), "+f"(d[19]), "+f"(d[20]), "+f"(d[21]), "+f"(d[22]), "+f"(d[23]), "+f"(d[24]), "+f"(d[25]), "+f"(d[26]), "+f"(d[27]), "+f"(d[28]), "+f"(d[29]), "+f"(d[30]), "+f"(d[31]), "+f"(d[32]), "+f"(d[33]), "+f"(d[34]), "+f"(d[35]), "+f"(d[36]), "+f"(d[37]), "+f"(d[38]), "+f"(d[39]), "+f"(d[40]), "+f"(d[41]), "+f"(d[42]), "+f"(d[43]), "+f"(d[44]), "+f"(d[45]), "+f"(d[46]), "+f"(d[47]), "+f"(d[48]), "+f"(d[49]), "+f"(d[50]), "+f"(d[51]), "+f"(d[52]), "+f"(d[53]), "+f"(d[54]), "+f"(d[55])
    : "l"(da), "l"(db), "r"(scale_d));
}
__device__ __forceinline__ void wgmma_ss_n112_t00(float* d, uint64_t da, uint64_t db, int scale_d) {
  asm volatile("{\n.reg .pred p;\nsetp.ne.b32 p, %58, 0;\n"
    "wgmma.mma_async.sync.aligned.m64n112k16.f32.bf16.bf16 "
    "{%0, %1, %2, %3, %4, %5, %6, %7, %8, %9, %10, %11, %12, %13, %14, %15, %16, %17, %18, %19, %20, %21, %22, %23, %24, %25, %26, %27, %28, %29, %30, %31, %32, %33, %34, %35, %36, %37, %38, %39, %40, %41, %42, %43, %44, %45, %46, %47, %48, %49, %50, %51, %52, %53, %54, %55}, "
    "%56, %57, p, 1, 1, 0, 0;\n}"
    : "+f"(d[0]), "+f"(d[1]), "+f"(d[2]), "+f"(d[3]), "+f"(d[4]), "+f"(d[5]), "+f"(d[6]), "+f"(d[7]), "+f"(d[8]), "+f"(d[9]), "+f"(d[10]), "+f"(d[11]), "+f"(d[12]), "+f"(d[13]), "+f"(d[14]), "+f"(d[15]), "+f"(d[16]), "+f"(d[17]), "+f"(d[18]), "+f"(d[19]), "+f"(d[20]), "+f"(d[21]), "+f"(d[22]), "+f"(d[23]), "+f"(d[24]), "+f"(d[25]), "+f"(d[26]), "+f"(d[27]), "+f"(d[28]), "+f"(d[29]), "+f"(d[30]), "+f"(d[31]), "+f"(d[32]), "+f"(d[33]), "+f"(d[34]), "+f"(d[35]), "+f"(d[36]), "+f"(d[37]), "+f"(d[38]), "+f"(d[39]), "+f"(d[40]), "+f"(d[41]), "+f"(d[42]), "+f"(d[43]), "+f"(d[44]), "+f"(d[45]), "+f"(d[46]), "+f"(d[47]), "+f"(d[48]), "+f"(d[49]), "+f"(d[50]), "+f"(d[51]), "+f"(d[52]), "+f"(d[53]), "+f"(d[54]), "+f"(d[55])
    : "l"(da), "l"(db), "r"(scale_d));
}
__device__ __forceinline__ void wgmma_ss_n120_t01(float* d, uint64_t da, uint64_t db, int scale_d) {
  asm volatile("{\n.reg .pred p;\nsetp.ne.b32 p, %62, 0;\n"
    "wgmma.mma_async.sync.aligned.m64n120k16.f32.bf16.bf16 "
    "{%0, %1, %2, %3, %4, %5, %6, %7, %8, %9, %10, %11, %12, %13, %14, %15, %16, %17, %18, %19, %20, %21, %22, %23, %24, %25, %26, %27, %28, %29, %30, %31, %32, %33, %34, %35, %36, %37, %38, %39, %40, %41, %42, %43, %44, %45, %46, %47, %48, %49, %50, %51, %52, %53, %54, %55, %56, %57, %58, %59}, "
    "%60, %61, p, 1, 1, 0, 1;\n}"
    : "+f"(d[0]), "+f"(d[1]), "+f"(d[2]), "+f"(d[3]), "+f"(d[4]), "+f"(d[5]), "+f"(d[6]), "+f"(d[7]), "+f"(d[8]), "+f"(d[9]), "+f"(d[10]), "+f"(d[11]), "+f"(d[12]), "+f"(d[13]), "+f"(d[14]), "+f"(d[15]), "+f"(d[16]), "+f"(d[17]), "+f"(d[18]), "+f"(d[19]), "+f"(d[20]), "+f"(d[21]), "+f"(d[22]), "+f"(d[23]), "+f"(d[24]), "+f"(d[25]), "+f"(d[26]), "+f"(d[27]), "+f"(d[28]), "+f"(d[29]), "+f"(d[30]), "+f"(d[31]), "+f"(d[32]), "+f"(d[33]), "+f"(d[34]), "+f"(d[35]), "+f"(d[36]), "+f"(d[37]), "+f"(d[38]), "+f"(d[39]), "+f"(d[40]), "+f"(d[41]), "+f"(d[42]), "+f"(d[43]), "+f"(d[44]), "+f"(d[45]), "+f"(d[46]), "+f"(d[47]), "+f"(d[48]), "+f"(d[49]), "+f"(d[50]), "+f"(d[51]), "+f"(d[52]), "+f"(d[53]), "+f"(d[54]), "+f"(d[55]), "+f"(d[56]), "+f"(d[57]), "+f"(d[58]), "+f"(d[59])
    : "l"(da), "l"(db), "r"(scale_d));
}
__device__ __forceinline__ void wgmma_ss_n56_t01(float* d, uint64_t da, uint64_t db, int scale_d) {
  asm volatile("{\n.reg .pred p;\nsetp.ne.b32 p, %30, 0;\n"
    "wgmma.mma_async.sync.aligned.m64n56k16.f32.bf16.bf16 "
    "{%0, %1, %2, %3, %4, %5, %6, %7, %8, %9, %10, %11, %12, %13, %14, %15, %16, %17, %18, %19, %20, %21, %22, %23, %24, %25, %26, %27}, "
    "%28, %29, p, 1, 1, 0, 1;\n}"
    : "+f"(d[0]), "+f"(d[1]), "+f"(d[2]), "+f"(d[3]), "+f"(d[4]), "+f"(d[5]), "+f"(d[6]), "+f"(d[7]), "+f"(d[8]), "+f"(d[9]), "+f"(d[10]), "+f"(d[11]), "+f"(d[12]), "+f"(d[13]), "+f"(d[14]), "+f"(d[15]), "+f"(d[16]), "+f"(d[17]), "+f"(d[18]), "+f"(d[19]), "+f"(d[20]), "+f"(d[21]), "+f"(d[22]), "+f"(d[23]), "+f"(d[24]), "+f"(d[25]), "+f"(d[26]), "+f"(d[27])
    : "l"(da), "l"(db), "r"(scale_d));
}
__device__ __forceinline__ void wgmma_ss_n64_t11(float* d, uint64_t da, uint64_t db, int scale_d) {
  asm volatile("{\n.reg .pred p;\nsetp.ne.b32 p, %34, 0;\n"
    "wgmma.mma_async.sync.aligned.m64n64k16.f32.bf16.bf16 "
    "{%0, %1, %2, %3, %4, %5, %6, %7, %8, %9, %10, %11, %12, %13, %14, %15, %16, %17, %18, %19, %20, %21, %22, %23, %24, %25, %26, %27, %28, %29, %30, %31}, "
    "%32, %33, p, 1, 1, 1, 1;\n}"
    : "+f"(d[0]), "+f"(d[1]), "+f"(d[2]), "+f"(d[3]), "+f"(d[4]), "+f"(d[5]), "+f"(d[6]), "+f"(d[7]), "+f"(d[8]), "+f"(d[9]), "+f"(d[10]), "+f"(d[11]), "+f"(d[12]), "+f"(d[13]), "+f"(d[14]), "+f"(d[15]), "+f"(d[16]), "+f"(d[17]), "+f"(d[18]), "+f"(d[19]), "+f"(d[20]), "+f"(d[21]), "+f"(d[22]), "+f"(d[23]), "+f"(d[24]), "+f"(d[25]), "+f"(d[26]), "+f"(d[27]), "+f"(d[28]), "+f"(d[29]), "+f"(d[30]), "+f"(d[31])
    : "l"(da), "l"(db), "r"(scale_d));
}
__device__ __forceinline__ void wgmma_ss_n64_t01(float* d, uint64_t da, uint64_t db, int scale_d) {
  asm volatile("{\n.reg .pred p;\nsetp.ne.b32 p, %34, 0;\n"
    "wgmma.mma_async.sync.aligned.m64n64k16.f32.bf16.bf16 "
    "{%0, %1, %2, %3, %4, %5, %6, %7, %8, %9, %10, %11, %12, %13, %14, %15, %16, %17, %18, %19, %20, %21, %22, %23, %24, %25, %26, %27, %28, %29, %30, %31}, "
    "%32, %33, p, 1, 1, 0, 1;\n}"
    : "+f"(d[0]), "+f"(d[1]), "+f"(d[2]), "+f"(d[3]), "+f"(d[4]), "+f"(d[5]), "+f"(d[6]), "+f"(d[7]), "+f"(d[8]), "+f"(d[9]), "+f"(d[10]), "+f"(d[11]), "+f"(d[12]), "+f"(d[13]), "+f"(d[14]), "+f"(d[15]), "+f"(d[16]), "+f"(d[17]), "+f"(d[18]), "+f"(d[19]), "+f"(d[20]), "+f"(d[21]), "+f"(d[22]), "+f"(d[23]), "+f"(d[24]), "+f"(d[25]), "+f"(d[26]), "+f"(d[27]), "+f"(d[28]), "+f"(d[29]), "+f"(d[30]), "+f"(d[31])
    : "l"(da), "l"(db), "r"(scale_d));
}
__device__ __forceinline__ void wgmma_rs_n56_t1(float* d, uint32_t a0, uint32_t a1, uint32_t a2, uint32_t a3, uint64_t db, int scale_d) {
  asm volatile("{\n.reg .pred p;\nsetp.ne.b32 p, %33, 0;\n"
    "wgmma.mma_async.sync.aligned.m64n56k16.f32.bf16.bf16 "
    "{%0, %1, %2, %3, %4, %5, %6, %7, %8, %9, %10, %11, %12, %13, %14, %15, %16, %17, %18, %19, %20, %21, %22, %23, %24, %25, %26, %27}, "
    "{%28, %29, %30, %31}, %32, p, 1, 1, 1;\n}"
    : "+f"(d[0]), "+f"(d[1]), "+f"(d[2]), "+f"(d[3]), "+f"(d[4]), "+f"(d[5]), "+f"(d[6]), "+f"(d[7]), "+f"(d[8]), "+f"(d[9]), "+f"(d[10]), "+f"(d[11]), "+f"(d[12]), "+f"(d[13]), "+f"(d[14]), "+f"(d[15]), "+f"(d[16]), "+f"(d[17]), "+f"(d[18]), "+f"(d[19]), "+f"(d[20]), "+f"(d[21]), "+f"(d[22]), "+f"(d[23]), "+f"(d[24]), "+f"(d[25]), "+f"(d[26]), "+f"(d[27])
    : "r"(a0), "r"(a1), "r"(a2), "r"(a3), "l"(db), "r"(scale_d));
}
__device__ __forceinline__ void wgmma_rs_n64_t1(float* d, uint32_t a0, uint32_t a1, uint32_t a2, uint32_t a3, uint64_t db, int scale_d) {
  asm volatile("{\n.reg .pred p;\nsetp.ne.b32 p, %37, 0;\n"
    "wgmma.mma_async.sync.aligned.m64n64k16.f32.bf16.bf16 "
    "{%0, %1, %2, %3, %4, %5, %6, %7, %8, %9, %10, %11, %12, %13, %14, %15, %16, %17, %18, %19, %20, %21, %22, %23, %24, %25, %26, %27, %28, %29, %30, %31}, "
    "{%32, %33, %34, %35}, %36, p, 1, 1, 1;\n}"
    : "+f"(d[0]), "+f"(d[1]), "+f"(d[2]), "+f"(d[3]), "+f"(d[4]), "+f"(d[5]), "+f"(d[6]), "+f"(d[7]), "+f"(d[8]), "+f"(d[9]), "+f"(d[10]), "+f"(d[11]), "+f"(d[12]), "+f"(d[13]), "+f"(d[14]), "+f"(d[15]), "+f"(d[16]), "+f"(d[17]), "+f"(d[18]), "+f"(d[19]), "+f"(d[20]), "+f"(d[21]), "+f"(d[22]), "+f"(d[23]), "+f"(d[24]), "+f"(d[25]), "+f"(d[26]), "+f"(d[27]), "+f"(d[28]), "+f"(d[29]), "+f"(d[30]), "+f"(d[31])
    : "r"(a0), "r"(a1), "r"(a2), "r"(a3), "l"(db), "r"(scale_d));
}

template <int V> struct IC { static constexpr int value = V; };
struct NoHook { template <class T> __device__ __forceinline__ void operator()(T) const {} };
template <int I, int N, class F> __device__ __forceinline__ void for_range(F&& f) {
  if constexpr (I < N) { f(IC<I>()); for_range<I + 1, N>(f); }
}
template <int N, int I = 0, class F> __device__ __forceinline__ void static_for(F&& f) {
  if constexpr (I < N) { f(IC<I>()); static_for<N, I + 1>(f); }
}

__host__ __device__ constexpr bool w_team_b(int n) { return n < 14; }
__host__ __device__ constexpr int w_par(int n) {
  int c = 0;
  for (int m = n & 3; m < n; m += NW) c += (w_team_b(m) == w_team_b(n));
  return c & 1;
}
__host__ __device__ constexpr bool r_team_b(int n) { return n < 32 || n >= 40; }
__host__ __device__ constexpr int r_par(int n) {
  int c = 0;
  for (int m = n % NSLOT; m < n; m += NSLOT) c += (r_team_b(m) == r_team_b(n));
  return c & 1;
}
__device__ __forceinline__ uint64_t desc_k_lo(uint32_t lo) { return (uint64_t)lo | (0x40000040ull << 32); }
__device__ __forceinline__ uint64_t launder(uint64_t x) { uint64_t y; asm("mov.b64 %0, %1;" : "=l"(y) : "l"(x)); return y; }
#define TP_PARAMS
#define TP_STAMP(s) do { } while (0)

template <int KIND, int N0, bool WAITX, class Hook>
__device__ __forceinline__ void consume1(float* acc, uint32_t sbase, int w, int lane, Hook hook TP_PARAMS) {
  const uint32_t bars = sbase + OFF_BAR;
  const uint32_t ax0 = ((sbase + OFF_X + w * 8192) >> 4) | 0x10000u;
  const uint64_t dw = launder(desc_mn(sbase + OFF_W));
  static_for<7>([&](auto si) {
    constexpr int s = decltype(si)::value, n = N0 + s, slot = n & (NW - 1);
    if (WAITX) mbar_wait_u(bars + BAR_XFULL + 8 * s, 0);
    mbar_wait_u(bars + (w_team_b(n) ? BAR_WFULLB : BAR_WFULLA) + 8 * slot, w_par(n));
    TP_STAMP(s);
    uint32_t ax = ax0;
    asm volatile("" : "+r"(ax));
    wg_fence();
#pragma unroll
    for (int k = 0; k < 4; k++) {
      if (KIND == 0) wgmma_ss_n112_t01(acc, desc_k_lo(ax + s * 1024 + 2 * k), dw + (slot * 1024 + 128 * k), (s | k) != 0);
      if (KIND == 2) wgmma_ss_n120_t01(acc, desc_k_lo(ax + s * 1024 + 2 * k), dw + (slot * 1024 + 128 * k), (s | k) != 0);
    }
    wg_commit();
    hook(si);
    if (s > 0) {
      wg_wait<1>();
      if (lane == 0) mbar_arrive(bars + BAR_WEMPTY + 8 * ((n - 1) & (NW - 1)));
    }
  });
  wg_wait<0>();
  if (lane == 0) mbar_arrive(bars + BAR_WEMPTY + 8 * ((N0 + 6) & (NW - 1)));
}
__device__ __forceinline__ void consume_q(float* acc, uint32_t sbase, int w, int lane TP_PARAMS) {
  const uint32_t bars = sbase + OFF_BAR;
  const uint32_t ax0 = ((sbase + OFF_X + w * 8192) >> 4) | 0x10000u;
  const uint64_t dw = launder(desc_mn(sbase + OFF_W));
  static_for<4>([&](auto si) {
    constexpr int s = decltype(si)::value, n = 21 + s, slot = n & (NW - 1);
    mbar_wait_u(bars + BAR_WFULLA + 8 * slot, w_par(n));
    TP_STAMP(s);
    uint32_t ax = ax0;
    asm volatile("" : "+r"(ax));
    wg_fence();
#pragma unroll
    for (int k = 0; k < 4; k++) wgmma_ss_n56_t01(acc, desc_k_lo(ax + 2 * s * 1024 + 2 * k), dw + (slot * 1024 + 128 * k), (s | k) != 0);
    if constexpr (s < 3) {
#pragma unroll
      for (int k = 0; k < 4; k++) wgmma_ss_n56_t01(acc, desc_k_lo(ax + (2 * s + 1) * 1024 + 2 * k), dw + (slot * 1024 + 512 + 128 * k), 1);
    }
    wg_commit();
    if (s > 0) {
      wg_wait<1>();
      if (lane == 0) mbar_arrive(bars + BAR_WEMPTY + 8 * ((n - 1) & (NW - 1)));
    }
  });
  wg_wait<0>();
  if (lane == 0) mbar_arrive(bars + BAR_WEMPTY + 8 * (24 & (NW - 1)));
}

template <int MODE, class Hook>
__device__ __forceinline__ void consume2(float* acc, uint32_t sbase, int w, int lane, Hook hook TP_PARAMS) {
  constexpr int N0 = MODE == 0 ? 0 : (MODE == 1 ? 32 : 40), NST = MODE == 0 ? 32 : (MODE == 1 ? 8 : 16);
  const uint32_t bars = sbase + OFF_BAR;
  const uint32_t ax0 = ((sbase + w * 8192) >> 4) | 0x10000u;
  const uint64_t db = launder(MODE == 0 ? desc_k(sbase + 16384) : desc_mn(sbase + 16384));
  auto stage = [&](auto si, uint32_t par, int sreal) {
    constexpr int s = decltype(si)::value, n = N0 + s, slot = n % NSLOT;
    mbar_wait_u(bars + (r_team_b(n) ? BAR_FULLB : BAR_FULLA) + 8 * slot, par);
    TP_STAMP(sreal);
    constexpr int aoff = (MODE == 2 && s == 0) ? OFF_SPARE / 16 : ((MODE == 2 && s == 1) ? (OFF_SC + SC_U1) / 16 : slot * (SLOT / 16));
    constexpr int boff = slot * (SLOT / 16), nk = (MODE == 2 && (s & 1)) ? 3 : 4;
    uint32_t ax = ax0;
    asm volatile("" : "+r"(ax));
    wg_fence();
#pragma unroll
    for (int k = 0; k < nk; k++) {
      if (MODE == 0) wgmma_ss_n112_t00(acc, desc_k_lo(ax + aoff + 2 * k), db + (boff + 2 * k), (s | k) != 0);
      else wgmma_ss_n64_t01(acc, desc_k_lo(ax + aoff + 2 * k), db + (boff + 128 * k), (s | k) != 0);
    }
    wg_commit();
    if (s > 0) {
      wg_wait<1>();
      if (lane == 0) mbar_arrive(bars + BAR_EMPTY + 8 * ((n + NSLOT - 1) % NSLOT));
    }
  };
  if constexpr (MODE == 0) {
    stage(IC<0>(), 0, 0);
    stage(IC<1>(), 0, 1);
#pragma unroll 1
    for (int it = 0; it < 6; it++) {
      const uint32_t p0 = it & 1, p1 = p0 ^ 1;
      stage(IC<2>(), p0, 2 + 5 * it);
      hook(it);
      stage(IC<3>(), p0, 3 + 5 * it);
      stage(IC<4>(), p0, 4 + 5 * it);
      stage(IC<5>(), p1, 5 + 5 * it);
      stage(IC<6>(), p1, 6 + 5 * it);
    }
  } else {
    static_for<NST>([&](auto si) { stage(si, r_par(N0 + decltype(si)::value), decltype(si)::value); });
  }
  wg_wait<0>();
  if (lane == 0) mbar_arrive(bars + BAR_EMPTY + 8 * ((N0 + NST - 1) % NSLOT));
}

__device__ __forceinline__ void feature_map(const float* p, uint32_t* out, int q) {
  const float L = 1.4426950408889634f;
  const bool lo = q < 2;
  float v[14], nx[14];
#pragma unroll
  for (int b = 0; b < 7; b++) {
    v[2 * b] = p[4 * b]; v[2 * b + 1] = p[4 * b + 1];
    nx[2 * b] = p[4 * b + 2]; nx[2 * b + 1] = p[4 * b + 3];
  }
#pragma unroll 1
  for (int r = 0; r < 2; r++) {
    float mx0 = fmaxf(fmaxf(fmaxf(v[0], v[1]), fmaxf(v[2], v[3])), fmaxf(v[4], v[5]));
    float mn0 = fminf(fminf(fminf(v[0], v[1]), fminf(v[2], v[3])), fminf(v[4], v[5]));
    float mx1 = fmaxf(fmaxf(fmaxf(v[8], v[9]), fmaxf(v[10], v[11])), fmaxf(v[12], v[13]));
    float mn1 = fminf(fminf(fminf(v[8], v[9]), fminf(v[10], v[11])), fminf(v[12], v[13]));
    const float mx3 = fmaxf(v[6], v[7]), mn3 = fminf(v[6], v[7]);
    if (lo) { mx0 = fmaxf(mx0, mx3); mn0 = fminf(mn0, mn3); } else { mx1 = fmaxf(mx1, mx3); mn1 = fminf(mn1, mn3); }
    mx0 = qmax(mx0); mx1 = qmax(mx1); mn0 = qmin(mn0); mn1 = qmin(mn1);
    const float a0 = -mx0 * L, a1 = -mx1 * L, c0 = mn0 * L, c1 = mn1 * L;
    const float a3 = lo ? a0 : a1, c3 = lo ? c0 : c1;
    float ep[14], em[14];
#pragma unroll
    for (int e = 0; e < 14; e++) {
      const float a = e < 6 ? a0 : (e < 8 ? a3 : a1), c = e < 6 ? c0 : (e < 8 ? c3 : c1);
      ep[e] = ex2f(fmaf(v[e], L, a));
      em[e] = ex2f(fmaf(v[e], -L, c));
    }
    float sp0 = ((ep[0] + ep[1]) + (ep[2] + ep[3])) + (ep[4] + ep[5]), sm0 = ((em[0] + em[1]) + (em[2] + em[3])) + (em[4] + em[5]);
    float sp1 = ((ep[8] + ep[9]) + (ep[10] + ep[11])) + (ep[12] + ep[13]), sm1 = ((em[8] + em[9]) + (em[10] + em[11])) + (em[12] + em[13]);
    const float sp3 = ep[6] + ep[7], sm3 = em[6] + em[7];
    if (lo) { sp0 += sp3; sm0 += sm3; } else { sp1 += sp3; sm1 += sm3; }
    const float rp0 = rcpf(qsum(sp0)), rp1 = rcpf(qsum(sp1)), rm0 = rcpf(qsum(sm0)), rm1 = rcpf(qsum(sm1));
    const float rp3 = lo ? rp0 : rp1, rm3 = lo ? rm0 : rm1;
#pragma unroll
    for (int b = 0; b < 7; b++) {
      const float rp = b < 3 ? rp0 : (b == 3 ? rp3 : rp1), rm = b < 3 ? rm0 : (b == 3 ? rm3 : rm1);
      ep[b] = __uint_as_float(pack2(ep[2 * b] * rp, ep[2 * b + 1] * rp));
      em[b] = __uint_as_float(pack2(em[2 * b] * rm, em[2 * b + 1] * rm));
    }
#pragma unroll
    for (int e = 0; e < 14; e++) { v[e] = nx[e]; nx[e] = e < 7 ? ep[e] : em[e - 7]; }
  }
#pragma unroll
  for (int b = 0; b < 7; b++) {
    out[2 * b] = __float_as_uint(v[b]); out[2 * b + 1] = __float_as_uint(nx[b]);
    out[14 + 2 * b] = __float_as_uint(v[7 + b]); out[14 + 2 * b + 1] = __float_as_uint(nx[7 + b]);
  }
}

template <int NB>
__device__ __forceinline__ void store_frag(uint32_t tile, int row0, const uint32_t* p, int lane) {
  const int m = lane >> 3, rr = lane & 7;
  const int row = row0 + 8 * (m & 1) + rr;
  const uint32_t ra = tile + row * 128;
#pragma unroll
  for (int b = 0; b + 1 < NB; b += 2) stsm4(ra + (((b + (m >> 1)) ^ rr) << 4), p[2 * b], p[2 * b + 1], p[2 * b + 2], p[2 * b + 3]);
  if (NB & 1) stsm2(ra + (((NB - 1) ^ rr) << 4), p[2 * (NB - 1)], p[2 * (NB - 1) + 1]);
}

__global__ void __launch_bounds__(NTHREADS, 1) fused_kernel(const __grid_constant__ Params P) {
  extern __shared__ uint8_t smem_raw[];
  const uint32_t sbase = (smem_u32(smem_raw) + 1023) & ~1023u;
  uint8_t* sgen = smem_raw + (sbase - smem_u32(smem_raw));
  const uint32_t sc = sbase + OFF_SC, bars = sbase + OFF_BAR;
  const int warp = __shfl_sync(~0u, (int)(threadIdx.x >> 5), 0), lane = threadIdx.x & 31;
  const int um = blockIdx.x >> 4, uh = ((blockIdx.x >> 3) ^ um) & 1;
  const int bi = 2 * um + ((blockIdx.x >> 2) & 1), bj = 4 * uh + (blockIdx.x & 3);
  unsigned* syncI = g_sync + bi * 32;
  unsigned* syncJ = g_sync + (16 + bj) * 32;

  if (warp >= 16) {
    asm volatile("setmaxnreg.dec.sync.aligned.u32 32;");
    auto init_range = [&](auto first) {
#pragma unroll
      for (int b = decltype(first)::value; b < decltype(first)::value + 15; b++) {
        const int off = 8 * b;
        int cnt = 1;
        if ((off >= BAR_WEMPTY && off < BAR_FULLB) || (off >= BAR_EMPTY && off < BAR_ZFREE) || off == BAR_SCFREE || off == BAR_RELRDY || off == BAR_GRDY || off == BAR_REL2RDY || off == BAR_XFREE) cnt = 8;
        if (off >= BAR_ZRDY && off < BAR_KVF) cnt = 4;
        mbar_init(bars + off, cnt);
      }
      asm volatile("fence.mbarrier_init.release.cluster;" ::: "memory");
    };
    if (warp == 16) {
      if (elect_one()) { prefetch_map(&P.x); prefetch_map(&P.win); init_range(IC<0>()); }
      __syncwarp();
      bar_arrive(8, NTHREADS);
      if (elect_one()) {
        TSTAMP(2, 17);
#pragma unroll
        for (int k = 0; k < 7; k++) {
          mbar_expect_tx(bars + BAR_XFULL + 8 * k, 16384);
          tma_ld2(sbase + OFF_X + k * 16384, &P.x, bars + BAR_XFULL + 8 * k, 64 * k, bi * 128);
          if (k < NW) {
            mbar_expect_tx(bars + BAR_WFULLB + 8 * k, 16384);
            tma_ld2(sbase + OFF_W + k * WSLOT, &P.win, bars + BAR_WFULLB + 8 * k, FH + 112 * bj, 64 * k);
            tma_ld2(sbase + OFF_W + k * WSLOT + 8192, &P.win, bars + BAR_WFULLB + 8 * k, FH + 112 * bj + 64, 64 * k);
          }
        }
        TSTAMP(2, 18);
      }
      __syncwarp();
      bar_sync(9, 128);
    } else {
      if (elect_one()) {
        if (warp == 17) init_range(IC<15>());
        else if (warp == 18) { init_range(IC<30>()); prefetch_map(&P.wq); }
        else init_range(IC<45>());
      }
      __syncwarp();
      bar_arrive(9, 128);
      bar_sync(8, NTHREADS);
    }
    if (!elect_one()) return;
    const int t0 = bi * 128;
    const unsigned epoch = ld_epoch(syncI + 8 + bj);
    if (warp == 16) {
      TSTAMP(2, 16);
#define PSTAMP() do { } while (0)
      int slot = 0;
      uint32_t eph = 0;
      auto wload = [&](const CUtensorMap* m, uint32_t full, int c0, int r0, int c1, int r1, bool two) {
        mbar_wait_u(bars + BAR_WEMPTY + 8 * slot, (eph >> slot) & 1);
        eph ^= 1u << slot;
        const uint32_t sw = sbase + OFF_W + slot * WSLOT, fb = bars + full + 8 * slot;
        mbar_expect_tx(fb, two ? 16384 : 8192);
        tma_ld2(sw, m, fb, c0, r0);
        if (two) tma_ld2(sw + 8192, m, fb, c1, r1);
        slot = (slot + 1) & (NW - 1);
        PSTAMP();
      };
#pragma unroll 1
      for (int k = NW; k < 7; k++) wload(&P.win, BAR_WFULLB, FH + 112 * bj, 64 * k, FH + 112 * bj + 64, 64 * k, true);
      TSTAMP(2, 0);
#pragma unroll 1
      for (int k = 0; k < 7; k++) wload(&P.win, BAR_WFULLB, 112 * bj, 64 * k, 112 * bj + 64, 64 * k, true);
      TSTAMP(2, 1);
      prefetch_map(&P.wsp); prefetch_map(&P.zt);
      poll_ge(g_sync + 25 * 32, (epoch + 1) * 128);
      fence_async_global();
      TSTAMP(2, 12);
#pragma unroll 1
      for (int k = 0; k < 7; k++) wload(&P.wq, BAR_WFULLA, 0, (8 + bj) * DM + 64 * k, 0, (16 + bj) * DM + 64 * k, true);
      TSTAMP(2, 2);
#pragma unroll 1
      for (int k = 0; k < 4; k++) wload(&P.wq, BAR_WFULLA, 0, bj * DM + 128 * k, 0, bj * DM + 128 * k + 64, k < 3);
      TSTAMP(2, 3);
      prefetch_map(&P.old); prefetch_map(&P.wo); prefetch_map(&P.uld); prefetch_map(&P.wout);
      unsigned* cntA = g_sync + 24 * 32;
      red_relaxed(cntA);
      poll_ge(syncJ + 0, (epoch + 1) * 16);
      int rs = 0;
      uint32_t rph = 0;
      auto rload = [&](uint32_t full, uint32_t bytes, const CUtensorMap* ma, int a0, int a1, bool with_a, const CUtensorMap* mb, int b0, int b1) {
        const uint32_t sa = sbase + rs * SLOT, fb = bars + full + 8 * rs;
        mbar_expect_tx(fb, bytes);
        if (with_a) tma_ld2(sa, ma, fb, a0, a1);
        tma_ld2(sa + 16384, mb, fb, b0, b1);
        rs = (rs == NSLOT - 1) ? 0 : rs + 1;
        PSTAMP();
      };
      auto rwait = [&]() { mbar_wait_u(bars + BAR_EMPTY + 8 * rs, (rph >> rs) & 1); rph ^= 1u << rs; };
#pragma unroll 1
      for (int k = 0; k < 32; k++) {
        if (k >= NSLOT) rwait();
        else {
          if (k < 4) { mbar_wait_u(bars + BAR_WEMPTY + 8 * slot, (eph >> slot) & 1); slot = (slot + 1) & (NW - 1); }
          if (k == 0) { TSTAMP(2, 11); poll_ge(cntA, (epoch + 1) * 128); fence_async_global(); TSTAMP(2, 4); }
        }
        rload(BAR_FULLB, 16384 + 14336, &P.wsp, 64 * k, t0, true, &P.zt, 64 * k, 112 * bj);
      }
      TSTAMP(2, 5);
      if (bj < 7) {
        mbar_wait_u(bars + BAR_OALL, 0);
        fence_async_global();
        TSTAMP(2, 6);
#pragma unroll 1
        for (int k = 0; k < 8; k++) {
          rwait();
          rload(BAR_FULLA, 24576, &P.old, 64 * k, t0, true, &P.wo, 64 * bj, 56 * k);
        }
        TSTAMP(2, 7);
        auto slc = [&](int k) { const int m = k >> 1; return m == 0 ? bj : (m - 1 < bj ? m - 1 : m); };
        const int rs0 = rs;
        int seen = -1;
        auto uwait = [&](int k) {
          const int sl = slc(k);
          if (sl != seen) { mbar_wait_u(bars + BAR_USL + 8 * sl, 0); fence_async_global(); seen = sl; }
        };
#pragma unroll 1
        for (int k = 0; k < 16; k++) {
          const int sl = slc(k);
          rwait();
          if (k >= NSLOT) uwait(k);
          rload(BAR_FULLB, k < 2 ? 8192 : 24576, &P.uld, sl * 128 + (k & 1) * 64, t0, k >= NSLOT, &P.wout, 64 * bj, sl * 112 + (k & 1) * 64);
          if (k == NSLOT - 1) {
            TSTAMP(2, 8);
#pragma unroll 1
            for (int m = 2; m < NSLOT; m++) {
              uwait(m);
              if (m == 2) TSTAMP(2, 9);
              const int r = (rs0 + m) % NSLOT;
              tma_ld2(sbase + r * SLOT, &P.uld, bars + BAR_FULLB + 8 * r, slc(m) * 128 + (m & 1) * 64, t0);
            }
          }
        }
        TSTAMP(2, 10);
      }
    } else if (warp == 17) {
#pragma unroll 1
      for (int w = 0; w < 2; w++) {
        mbar_wait_u(bars + BAR_ZRDY + 8 * w, 0);
        tma_st2(&P.zt, sc + SC_ZSTG + w * 14336, t0 + 64 * w, 112 * bj);
      }
      bulk_commit();
      TSTAMP(1, 12);
      bulk_wait_read();
      TSTAMP(1, 13);
      mbar_arrive(bars + BAR_ZFREE);
      bulk_wait_all();
      red_release(syncJ + 0);
#pragma unroll 1
      for (int w = 0; w < 2; w++) {
        mbar_wait_u(bars + BAR_URDY + 8 * w, 0);
        tma_st2(&P.ust, sbase + OFF_SPARE + w * 8192, 128 * bj, t0 + 64 * w);
        tma_st2(&P.ust, sc + SC_U1 + w * 8192, 128 * bj + 64, t0 + 64 * w);
      }
      bulk_commit();
      TSTAMP(2, 13);
      bulk_wait_all();
      TSTAMP(2, 14);
      red_release(syncI + 16 + bj);
      TSTAMP(2, 15);
      if (bj < 7) {
        uint32_t pend = 0xffu & ~(1u << bj), it = 0;
        while (pend && ++it < (1u << 20)) {
          const uint4 a = ld_relaxed4(reinterpret_cast<const uint4*>(syncI + 16)), b = ld_relaxed4(reinterpret_cast<const uint4*>(syncI + 20));
          const uint32_t v[8] = {a.x, a.y, a.z, a.w, b.x, b.y, b.z, b.w};
#pragma unroll
          for (int j = 0; j < 8; j++)
            if (((pend >> j) & 1) && (int)(v[j] - (epoch + 1)) >= 0) { mbar_arrive(bars + BAR_USL + 8 * j); pend &= ~(1u << j); }
        }
      }
    } else if (warp == 18) {
      const int cta = bi * 8 + bj;
      mbar_wait_u(bars + BAR_RELRDY, 0);
      TSTAMP(2, 28);
      bulk_st(reinterpret_cast<uint8_t*>(g_Wq) + cta * 10752, sc + SC_RELAY, 10752);
      bulk_commit();
      bulk_wait_all();
      red_release(g_sync + 25 * 32);
      TSTAMP(2, 29);
      mbar_arrive(bars + BAR_RELDONE);
      mbar_wait_u(bars + BAR_GRDY, 0);
      bulk_st(g_KV + bj * 3584 + bi * 224, sc + SC_WPHI + 56 * 128, 896);
      bulk_st(g_gate + t0 + bj * 16, bars + OFF_GATE, 64);
      bulk_commit();
      bulk_wait_all();
      red_release(syncJ + 2);
      poll_ge(syncJ + 2, (epoch + 1) * 16);
#pragma unroll 1
      for (int w = 0; w < 2; w++) {
        mbar_wait_u(bars + BAR_KDRDY + 8 * w, 0);
        bulk_reduce_f32(g_KV + bj * 3584, sc + SC_KVS + w * 16384, 14336);
      }
      TSTAMP(2, 20);
      bulk_commit();
      bulk_wait_all();
      red_release(syncJ + 1);
      TSTAMP(2, 21);
      poll_ge(syncJ + 1, (epoch + 1) * 16);
      TSTAMP(2, 22);
      fence_async_global();
      mbar_expect_tx(bars + BAR_KVF, 14336);
      bulk_ld(sc + SC_KVF, g_KV + bj * 3584, 14336, bars + BAR_KVF);
    } else {
#pragma unroll 1
      for (int w = 0; w < 2; w++) {
        mbar_wait_u(bars + BAR_ORDY + 8 * w, 0);
        tma_st2(&P.ost, sc + SC_OSTG + w * 8192, 64 * bj, t0 + 64 * w);
      }
      bulk_commit();
      bulk_wait_all();
      red_release(syncI + 2);
      TSTAMP(2, 23);
      poll_ge(syncI + 2, (epoch + 1) * 8);
      TSTAMP(2, 24);
      mbar_arrive(bars + BAR_OALL);
    }
  } else if (warp < 8) {
    bar_sync(8, NTHREADS);
    if (threadIdx.x == 0) TSTAMP(0, 18);
    asm volatile("setmaxnreg.inc.sync.aligned.u32 %0;" ::"n"(REGS_B));
    if (threadIdx.x == 0) TSTAMP(0, 19);
    const int w = warp >> 2, ww = warp & 3, q = lane & 3;
    const int r0 = 64 * w + 16 * ww + (lane >> 2);
    unsigned epoch;
    uint2* strec = g_stats + bi * 1024 + r0;
    float acc[56];
    consume1<0, 0, true>(acc, sbase, w, lane, [&](auto si) {
      if (decltype(si)::value == 0) {
        epoch = ld_epoch(syncI + 8 + bj);
        if (q == 0) {
          st_relaxed2(strec + 128 * bj, make_uint2(0, 0));
          st_relaxed2(strec + 128 * bj + 8, make_uint2(0, 0));
        }
      }
    } TP(0));
    reg_fence<56>(acc);
    if (threadIdx.x == 0) TSTAMP(0, 0);
    {
      float s0 = 0.f, s1 = 0.f;
#pragma unroll
      for (int b = 0; b < 14; b++) {
        acc[4 * b] = gelu2_f(acc[4 * b]); acc[4 * b + 1] = gelu2_f(acc[4 * b + 1]);
        acc[4 * b + 2] = gelu2_f(acc[4 * b + 2]); acc[4 * b + 3] = gelu2_f(acc[4 * b + 3]);
        s0 += acc[4 * b] + acc[4 * b + 1];
        s1 += acc[4 * b + 2] + acc[4 * b + 3];
      }
      const float m0 = qsum(s0) * (1.f / 112.f), m1 = qsum(s1) * (1.f / 112.f);
      float v0 = 0.f, v1 = 0.f;
#pragma unroll
      for (int b = 0; b < 14; b++) {
        float d0 = acc[4 * b] - m0, d1 = acc[4 * b + 1] - m0, d2 = acc[4 * b + 2] - m1, d3 = acc[4 * b + 3] - m1;
        v0 = fmaf(d0, d0, v0); v0 = fmaf(d1, d1, v0);
        v1 = fmaf(d2, d2, v1); v1 = fmaf(d3, d3, v1);
      }
      v0 = qsum(v0); v1 = qsum(v1);
      if (q == 0) {
        const uint32_t tag = 1 + epoch % 3;
        st_relaxed2(strec + 128 * bj, make_uint2(__float_as_uint(m0), (__float_as_uint(v0) & ~3u) | tag));
        st_relaxed2(strec + 128 * bj + 8, make_uint2(__float_as_uint(m1), (__float_as_uint(v1) & ~3u) | tag));
      }
    }
    uint32_t z2[28];
#pragma unroll
    for (int b = 0; b < 14; b++) {
      z2[2 * b] = pack2(acc[4 * b], acc[4 * b + 1]);
      z2[2 * b + 1] = pack2(acc[4 * b + 2], acc[4 * b + 3]);
    }
    if (threadIdx.x == 0) TSTAMP(0, 1);
    uint32_t z1[28];
    uint2 ra, rb, rc, rd;
    {
      float a1[56];
      consume1<0, 7, false>(a1, sbase, w, lane, [&](auto si) {
        if (decltype(si)::value == STATS_AT) {
          ra = ld_relaxed2(strec + 256 * q); rb = ld_relaxed2(strec + 256 * q + 128);
          rc = ld_relaxed2(strec + 256 * q + 8); rd = ld_relaxed2(strec + 256 * q + 128 + 8);
        }
      } TP(7));
      reg_fence<56>(a1);
      if (threadIdx.x == 0) TSTAMP(0, 4);
#pragma unroll
      for (int b = 0; b < 14; b++) {
        z1[2 * b] = pack2(a1[4 * b], a1[4 * b + 1]);
        z1[2 * b + 1] = pack2(a1[4 * b + 2], a1[4 * b + 3]);
      }
    }
    {
      {
        const uint32_t tag = 1 + epoch % 3;
        uint32_t it = 0;
        while (true) {
          const bool ok = (ra.y & 3u) == tag && (rb.y & 3u) == tag && (rc.y & 3u) == tag && (rd.y & 3u) == tag;
          if (__all_sync(~0u, ok) || ++it > (1u << 20)) break;
          ra = ld_relaxed2(strec + 256 * q); rb = ld_relaxed2(strec + 256 * q + 128);
          rc = ld_relaxed2(strec + 256 * q + 8); rd = ld_relaxed2(strec + 256 * q + 128 + 8);
        }
      }
      if (threadIdx.x == 0) TSTAMP(0, 2);
      const float4 a = make_float4(__uint_as_float(ra.x), __uint_as_float(ra.y & ~3u), __uint_as_float(rb.x), __uint_as_float(rb.y & ~3u));
      const float4 c = make_float4(__uint_as_float(rc.x), __uint_as_float(rc.y & ~3u), __uint_as_float(rd.x), __uint_as_float(rd.y & ~3u));
      const float m0 = qsum(a.x + a.z) * 0.125f, m1 = qsum(c.x + c.z) * 0.125f;
      const float e0 = a.x - m0, e1 = a.z - m0, e2 = c.x - m1, e3 = c.z - m1;
      const float v0 = qsum(a.y + a.w + 112.f * (e0 * e0 + e1 * e1)) * (1.f / 896.f);
      const float v1 = qsum(c.y + c.w + 112.f * (e2 * e2 + e3 * e3)) * (1.f / 896.f);
      const float rs0 = rsqrtf(v0 + 4e-5f), rs1 = rsqrtf(v1 + 4e-5f);
      const float o0 = -m0 * rs0, o1 = -m1 * rs1;
      const uint32_t stg = sc + SC_ZSTG + w * 14336;
      mbar_wait_u(bars + BAR_RELDONE, 0);
      const int m = lane >> 3, rr = lane & 7;
      const uint32_t cofs = (uint32_t)(((2 * ww + (m & 1)) ^ rr) << 4);
#pragma unroll
      for (int b = 0; b < 14; b += 2) {
        auto nrm = [](uint32_t v, float rs, float o) { return pack2(fmaf(__uint_as_float(v << 16), rs, o), fmaf(__uint_as_float(v & 0xffff0000u), rs, o)); };
        const uint32_t p0 = nrm(z2[2 * b], rs0, o0), p1 = nrm(z2[2 * b + 1], rs1, o1), p2 = nrm(z2[2 * b + 2], rs0, o0), p3 = nrm(z2[2 * b + 3], rs1, o1);
        stsm4t(stg + (8 * (b + (m >> 1)) + rr) * 128 + cofs, p0, p1, p2, p3);
      }
      fence_async_smem();
      __syncwarp();
      if (lane == 0) mbar_arrive(bars + BAR_ZRDY + 8 * w);
    }
    if (threadIdx.x == 0) TSTAMP(0, 3);
#pragma unroll
    for (int c = 0; c < 28; c++) z1[c] = gelu2_pack(z1[c]);
    if (threadIdx.x == 0) TSTAMP(0, 5);
    float bs0, bs1;
    float g[56];
    consume2<0>(g, sbase, w, lane, [&](int it) {
      if (it == 5) { bs0 = 0.5f * __bfloat162float(P.bsp[bi * 128 + r0]); bs1 = 0.5f * __bfloat162float(P.bsp[bi * 128 + r0 + 8]); }
    } TP(28));
    reg_fence<56>(g);
    if (threadIdx.x == 0) TSTAMP(0, 6);
    {
      uint32_t u[28];
#pragma unroll
      for (int b = 0; b < 14; b++) {
        float a0 = __uint_as_float(z1[2 * b] << 16), a1 = __uint_as_float(z1[2 * b] & 0xffff0000u);
        float a2 = __uint_as_float(z1[2 * b + 1] << 16), a3 = __uint_as_float(z1[2 * b + 1] & 0xffff0000u);
        u[2 * b] = pack2(a0 * fmaf(g[4 * b], 0.5f, bs0), a1 * fmaf(g[4 * b + 1], 0.5f, bs0));
        u[2 * b + 1] = pack2(a2 * fmaf(g[4 * b + 2], 0.5f, bs1), a3 * fmaf(g[4 * b + 3], 0.5f, bs1));
      }
      if (threadIdx.x == 0) TSTAMP(0, 21);
      mbar_wait(bars + BAR_SCFREE, 0);
      store_frag<8>(sbase + OFF_SPARE, 64 * w + 16 * ww, u, lane);
      store_frag<6>(sc + SC_U1, 64 * w + 16 * ww, u + 16, lane);
      fence_async_smem();
      __syncwarp();
      if (lane == 0) mbar_arrive(bars + BAR_URDY + 8 * w);
    }
    if (threadIdx.x == 0) TSTAMP(0, 7);
    if (bj < 7) {
      float acc[32];
      bar_sync(1 + w, 128);
      consume2<2>(acc, sbase, w, lane, NoHook() TP(68));
      reg_fence<32>(acc);
      if (threadIdx.x == 0) TSTAMP(0, 8);
      bar_sync(6, 512);
      const float* ap = reinterpret_cast<const float*>(sgen + OFF_SC + SC_APART) + (threadIdx.x & 255);
      const float* gs = reinterpret_cast<const float*>(sgen + OFF_BAR + OFF_GATE);
      const float g0 = 1.f - gs[r0], g1 = 1.f - gs[r0 + 8];
      uint32_t o[16];
#pragma unroll
      for (int b = 0; b < 8; b++) {
        o[2 * b] = pack2(fmaf(acc[4 * b], g0, ap[(4 * b) * 256]), fmaf(acc[4 * b + 1], g0, ap[(4 * b + 1) * 256]));
        o[2 * b + 1] = pack2(fmaf(acc[4 * b + 2], g1, ap[(4 * b + 2) * 256]), fmaf(acc[4 * b + 3], g1, ap[(4 * b + 3) * 256]));
      }
      store_frag<8>(sbase + OFF_SPARE, 64 * w + 16 * ww, o, lane);
      fence_async_smem();
      bar_sync(1 + w, 128);
      if (ww == 0 && lane == 0) {
        tma_st2(&P.out, sbase + OFF_SPARE + w * 8192, 64 * bj, bi * 128 + 64 * w);
        bulk_commit();
        bulk_wait_read();
      }
    }
    if (threadIdx.x == 0) syncI[8 + bj] = ld_epoch(syncI + 8 + bj) + 1;
    if (threadIdx.x == 0) TSTAMP(0, 9);
  } else {
    bar_sync(8, NTHREADS);
    asm volatile("setmaxnreg.inc.sync.aligned.u32 %0;" ::"n"(REGS_A));
    const int tid = threadIdx.x - 256;
    const int w = (warp >> 2) & 1, ww = warp & 3, q = lane & 3;
    const int wrow = 64 * w + 16 * ww;
    const int r0 = wrow + (lane >> 2);
    const int cta = bi * 8 + bj;
    {
      uint4 rq[3];
#pragma unroll
      for (int m = 0; m < 3; m++) {
        const int t = tid + 256 * m, r = 84 * cta + (t >> 3), ch = t & 7, seg = r / DM, k = r - seg * DM;
        rq[m] = make_uint4(0, 0, 0, 0);
        if (t < 672 && ch < 7) rq[m] = __ldg(reinterpret_cast<const uint4*>(P.wqkv_ptr + k * 1344 + seg * 56 + ch * 8));
      }
      const __nv_bfloat16* wsrc = P.wphi + bj * 2 * 784;
      uint32_t wv[4];
#pragma unroll
      for (int m = 0; m < 4; m++) { const int e = tid + 256 * m; wv[m] = e < 784 ? __ldg(reinterpret_cast<const uint32_t*>(wsrc) + e) : 0u; }
      const int gl = tid & 15;
      uint2 gv[7];
#pragma unroll
      for (int m = 0; m < 7; m++) gv[m] = __ldg(reinterpret_cast<const uint2*>(P.gatew + 64 * m + 4 * gl));
      uint4* wp = reinterpret_cast<uint4*>(sgen + OFF_SC + SC_WPHI);
      wp[tid] = make_uint4(0, 0, 0, 0);
      wp[tid + 256] = make_uint4(0, 0, 0, 0);
      uint4* rs = reinterpret_cast<uint4*>(sgen + OFF_SC + SC_RELAY);
#pragma unroll
      for (int m = 0; m < 3; m++) { const int t = tid + 256 * m; if (t < 672) rs[t] = rq[m]; }
      fence_async_smem();
      __syncwarp();
      if (lane == 0) mbar_arrive(bars + BAR_RELRDY);
      bar_sync(5, 256);
      uint32_t* wt = reinterpret_cast<uint32_t*>(sgen + OFF_SC + SC_WPHI);
#pragma unroll
      for (int m = 0; m < 4; m++) {
        const int e = tid + 256 * m;
        if (e < 784) {
          const int h = e >= 392, rem = e - h * 392, d = rem / 14, f = 2 * (rem - d * 14);
          const int k = 28 * h + d, n = 28 * h + f;
          wt[k * 32 + ((((n >> 3) ^ (k & 7)) << 2) | ((n & 7) >> 1))] = wv[m];
        }
      }
      {
        const int grow = bj * 16 + (tid >> 4);
        const uint8_t* xrow = sgen + OFF_X + grow * 128 + (((gl >> 1) ^ (grow & 7)) << 4) + (gl & 1) * 8;
        float gsum = 0.f;
#pragma unroll
        for (int m = 0; m < 7; m++) {
          mbar_wait_u(bars + BAR_XFULL + 8 * m, 0);
          const uint2 xv = *reinterpret_cast<const uint2*>(xrow + m * 16384);
          gsum = fmaf(__uint_as_float(xv.x << 16), __uint_as_float(gv[m].x << 16), gsum);
          gsum = fmaf(__uint_as_float(xv.x & 0xffff0000u), __uint_as_float(gv[m].x & 0xffff0000u), gsum);
          gsum = fmaf(__uint_as_float(xv.y << 16), __uint_as_float(gv[m].y << 16), gsum);
          gsum = fmaf(__uint_as_float(xv.y & 0xffff0000u), __uint_as_float(gv[m].y & 0xffff0000u), gsum);
        }
#pragma unroll
        for (int o = 8; o > 0; o >>= 1) gsum += __shfl_xor_sync(~0u, gsum, o);
        if (gl == 0) reinterpret_cast<float*>(sgen + OFF_BAR + OFF_GATE)[tid >> 4] = 1.f / (1.f + __expf(-gsum));
      }
      fence_async_smem();
      __syncwarp();
      if (lane == 0) mbar_arrive(bars + BAR_GRDY);
      bar_sync(5, 256);
    }
    if (tid == 0) TSTAMP(1, 0);
    prefetch_l2(reinterpret_cast<const char*>(P.wsp_ptr) + (size_t)(cta * 16 + (tid >> 4)) * 4096 + (tid & 15) * 128);
    mbar_wait_u(bars + BAR_WFULLA + 8 * (14 & 3), 0);
    prefetch_l2(reinterpret_cast<const char*>(P.wsp_ptr) + (size_t)(cta * 16 + (tid >> 4)) * 4096 + 2048 + (tid & 15) * 128);
    const uint64_t dWphi = desc_mn(sc + SC_WPHI);
    uint32_t kp[16], vp[16], qp[14];
    {
      float acc[60];
      consume1<2, 14, false>(acc, sbase, w, lane, NoHook() TP(14));
      reg_fence<60>(acc);
      if (tid == 0) TSTAMP(1, 1);
#pragma unroll
      for (int b = 0; b < 7; b++) {
        vp[2 * b] = pack2(acc[32 + 4 * b], acc[32 + 4 * b + 1]);
        vp[2 * b + 1] = pack2(acc[32 + 4 * b + 2], acc[32 + 4 * b + 3]);
      }
      vp[14] = vp[15] = (q == 0) ? 0x00003f80u : 0u;
#pragma unroll
      for (int i = 0; i < 16; i++) kp[i] = pack2(acc[2 * i], acc[2 * i + 1]);
    }
    {
      float accq[28];
      consume_q(accq, sbase, w, lane TP(21));
      reg_fence<28>(accq);
      if (tid == 0) TSTAMP(1, 2);
#pragma unroll
      for (int i = 0; i < 14; i++) qp[i] = pack2(accq[2 * i], accq[2 * i + 1]);
    }
    {
      const uint32_t tV = sc + SC_KVS + w * 16384, tP = tV + 8192;
      mbar_wait(bars + BAR_ZFREE, 0);
      store_frag<8>(tV, 16 * ww, vp, lane);
      float pk[28];
      wg_fence();
#pragma unroll
      for (int k = 0; k < 4; k++) wgmma_rs_n56_t1(pk, kp[4 * k], kp[4 * k + 1], kp[4 * k + 2], kp[4 * k + 3], dWphi + 128 * k, k != 0);
      wg_commit();
      wg_wait<0>();
      reg_fence<28>(pk);
      uint32_t f[28];
      feature_map(pk, f, q);
      if (tid == 0) TSTAMP(1, 3);
      const uint64_t dA = desc_mn(tP), dB = desc_mn(tV);
      float kv0[32], kv1[32];
      store_frag<7>(tP, 16 * ww, f, lane);
      fence_async_smem();
      bar_sync(3 + w, 128);
      wg_fence();
#pragma unroll
      for (int k = 0; k < 4; k++) wgmma_ss_n64_t11(kv0, dA + 128 * k, dB + 128 * k, k != 0);
      wg_commit();
      wg_wait<0>();
      reg_fence<32>(kv0);
      bar_sync(3 + w, 128);
      store_frag<7>(tP, 16 * ww, f + 14, lane);
      fence_async_smem();
      bar_sync(3 + w, 128);
      wg_fence();
#pragma unroll
      for (int k = 0; k < 4; k++) wgmma_ss_n64_t11(kv1, dA + 128 * k, dB + 128 * k, k != 0);
      wg_commit();
      wg_wait<0>();
      reg_fence<32>(kv1);
      bar_sync(3 + w, 128);
      float* kd = reinterpret_cast<float*>(sgen + OFF_SC + SC_KVS + w * 16384);
#pragma unroll
      for (int sg = 0; sg < 2; sg++) {
        const float* kv = sg ? kv1 : kv0;
#pragma unroll
        for (int r = 0; r < 2; r++) {
          const int c = 16 * ww + (lane >> 2) + 8 * r;
          if (c < 56) {
            const int lo = c >= 28 ? 28 : 0, k = 56 * sg + c, sw = (k & 7) << 2;
            float* dst = kd + k * 32;
#pragma unroll
            for (int b = 0; b < 8; b++) {
              const int n = 8 * b + 2 * q;
              if (n >= lo && n < lo + 28) *reinterpret_cast<float2*>(dst + ((n - lo) ^ sw)) = make_float2(kv[4 * b + 2 * r], kv[4 * b + 2 * r + 1]);
              if (n == 56) *reinterpret_cast<float2*>(dst + (28 ^ sw)) = make_float2(kv[4 * b + 2 * r], 0.f);
              if (n == 58) *reinterpret_cast<float2*>(dst + (30 ^ sw)) = make_float2(0.f, 0.f);
            }
          }
        }
      }
      fence_async_smem();
      __syncwarp();
      if (lane == 0) mbar_arrive(bars + BAR_KDRDY + 8 * w);
    }
    if (tid == 0) TSTAMP(1, 4);
    uint32_t fq[28];
    {
      float pq[28];
      wg_fence();
#pragma unroll
      for (int k = 0; k < 3; k++) wgmma_rs_n56_t1(pq, qp[4 * k], qp[4 * k + 1], qp[4 * k + 2], qp[4 * k + 3], dWphi + 128 * k, k != 0);
      wgmma_rs_n56_t1(pq, qp[12], qp[13], 0u, 0u, dWphi + 128 * 3, 1);
      wg_commit();
      wg_wait<0>();
      reg_fence<28>(pq);
      if (lane == 0) mbar_arrive(bars + BAR_SCFREE);
      feature_map(pq, fq, q);
    }
    if (tid == 0) TSTAMP(1, 6);
    if (tid < 49) prefetch_l2(reinterpret_cast<const char*>(P.wout_ptr) + cta * 6272 + tid * 128);
    else if (tid >= 64 && tid < 64 + 25) prefetch_l2(reinterpret_cast<const char*>(P.wo_ptr) + cta * 3136 + (tid - 64) * 128);
    mbar_wait(bars + BAR_KVF, 0);
    if (tid == 0) TSTAMP(1, 7);
    {
      const float* kf = reinterpret_cast<const float*>(sgen + OFF_SC + SC_KVF);
#pragma unroll
      for (int m = 0; m < 4; m++) {
        const int it = tid + 256 * m;
        if (it < 112 * 8) {
          const int k = it >> 3, ch = it & 7, sw = (k & 7) << 2;
          const int hc = (k >= 56 ? k - 56 : k) >= 28;
          uint32_t v[4];
#pragma unroll
          for (int e = 0; e < 4; e++) {
            const int d = 8 * ch + 2 * e - 28 * hc;
            float2 x = make_float2(0.f, 0.f);
            if (ch < 7 && d >= 0 && d < 28) x = *reinterpret_cast<const float2*>(kf + k * 32 + (d ^ sw));
            if (ch == 7 && e == 0) { const float z = kf[k * 32 + (28 ^ sw)]; x = hc ? make_float2(0.f, z) : make_float2(z, 0.f); }
            v[e] = pack2(x.x, x.y);
          }
          *reinterpret_cast<uint4*>(sgen + OFF_SC + SC_KVB + k * 128 + ((ch ^ (k & 7)) << 4)) = make_uint4(v[0], v[1], v[2], v[3]);
        }
      }
      fence_async_smem();
      bar_sync(5, 256);
      if (tid == 0) TSTAMP(1, 11);
      float o[32];
      const uint64_t dB = desc_mn(sc + SC_KVB);
      wg_fence();
#pragma unroll
      for (int k = 0; k < 7; k++) wgmma_rs_n64_t1(o, fq[4 * k], fq[4 * k + 1], fq[4 * k + 2], fq[4 * k + 3], dB + 128 * k, k != 0);
      wg_commit();
      wg_wait<0>();
      reg_fence<32>(o);
      uint32_t op[16];
#pragma unroll
      for (int r = 0; r < 2; r++) {
        const float d0 = __shfl_sync(~0u, o[28 + 2 * r], lane & ~3), d1 = __shfl_sync(~0u, o[29 + 2 * r], lane & ~3);
        const float i0 = rcpf(d0 + 1e-6f), i1 = rcpf(d1 + 1e-6f), i3 = q < 2 ? i0 : i1;
#pragma unroll
        for (int b = 0; b < 7; b++) {
          const float iv = b < 3 ? i0 : (b == 3 ? i3 : i1);
          op[2 * b + r] = pack2(o[4 * b + 2 * r] * iv, o[4 * b + 2 * r + 1] * iv);
        }
      }
      op[14] = op[15] = 0u;
      store_frag<8>(sc + SC_OSTG, wrow, op, lane);
      fence_async_smem();
      __syncwarp();
      if (lane == 0) mbar_arrive(bars + BAR_ORDY + 8 * w);
    }
    if (tid == 0) TSTAMP(1, 8);
    if (bj < 7) {
      float acc[32];
      consume2<1>(acc, sbase, w, lane, NoHook() TP(60));
      reg_fence<32>(acc);
      if (tid == 0) TSTAMP(1, 9);
      mbar_wait(bars + BAR_OALL, 0);
      const float g0 = __ldcg(g_gate + bi * 128 + r0), g1 = __ldcg(g_gate + bi * 128 + r0 + 8);
      bar_sync(5, 256);
      float* ap = reinterpret_cast<float*>(sgen + OFF_SC + SC_APART) + tid;
#pragma unroll
      for (int b = 0; b < 8; b++) {
        ap[(4 * b) * 256] = acc[4 * b] * g0;
        ap[(4 * b + 1) * 256] = acc[4 * b + 1] * g0;
        ap[(4 * b + 2) * 256] = acc[4 * b + 2] * g1;
        ap[(4 * b + 3) * 256] = acc[4 * b + 3] * g1;
      }
      if (q == 0) {
        float* gs = reinterpret_cast<float*>(sgen + OFF_BAR + OFF_GATE);
        gs[r0] = g0; gs[r0 + 8] = g1;
      }
      bar_arrive(6, 512);
    }
    if (tid == 0) TSTAMP(1, 10);
  }
}

typedef CUresult (*EncodeFn)(CUtensorMap*, CUtensorMapDataType, cuuint32_t, void*, const cuuint64_t*, const cuuint64_t*, const cuuint32_t*,
                             const cuuint32_t*, CUtensorMapInterleave, CUtensorMapSwizzle, CUtensorMapL2promotion, CUtensorMapFloatOOBfill);

static void map2(EncodeFn fn, CUtensorMap* m, const void* p, uint64_t rows, uint64_t cols, uint32_t brows, uint32_t bcols,
                 CUtensorMapL2promotion promo = CU_TENSOR_MAP_L2_PROMOTION_L2_128B) {
  cuuint64_t gd[2] = {cols, rows};
  cuuint64_t gs[1] = {cols * 2};
  cuuint32_t bd[2] = {bcols, brows};
  cuuint32_t es[2] = {1, 1};
  fn(m, CU_TENSOR_MAP_DATA_TYPE_BFLOAT16, 2, const_cast<void*>(p), gd, gs, bd, es, CU_TENSOR_MAP_INTERLEAVE_NONE, CU_TENSOR_MAP_SWIZZLE_128B,
     promo, CU_TENSOR_MAP_FLOAT_OOB_FILL_NONE);
}

}

extern "C" void kernel_launch(void* const* d_in, const int* in_sizes, int n_in, void* d_out, int out_size) {
  using namespace hk;
  (void)in_sizes; (void)n_in; (void)out_size;
  static EncodeFn fn = nullptr;
  static void *pZT, *pU, *pO, *pWq;
  if (!fn) {
    void* p = nullptr;
    cudaDriverEntryPointQueryResult qr;
    cudaGetDriverEntryPoint("cuTensorMapEncodeTiled", &p, cudaEnableDefault, &qr);
    fn = (EncodeFn)p;
    cudaGetSymbolAddress(&pZT, g_ZT);
    cudaGetSymbolAddress(&pU, g_U);
    cudaGetSymbolAddress(&pO, g_O);
    cudaGetSymbolAddress(&pWq, g_Wq);
    cudaFuncSetAttribute(fused_kernel, cudaFuncAttributeMaxDynamicSharedMemorySize, SMEM_BYTES);
  }
  Params P = {};
  map2(fn, &P.x, d_in[0], SEQ, DM, 128, 64);
  map2(fn, &P.win, d_in[5], DM, 2 * FH, 64, 64);
  map2(fn, &P.wq, pWq, 24 * DM, 64, 64, 64);
  map2(fn, &P.ost, pO, SEQ, 512, 64, 64);
  map2(fn, &P.wsp, d_in[6], SEQ, SEQ, 128, 64);
  map2(fn, &P.zt, pZT, FH, SEQ, 112, 64);
  map2(fn, &P.ust, pU, SEQ, 1024, 64, 64);
  map2(fn, &P.uld, pU, SEQ, 1024, 128, 64);
  map2(fn, &P.old, pO, SEQ, 512, 128, 64);
  map2(fn, &P.wout, d_in[8], FH, DM, 64, 64);
  map2(fn, &P.wo, d_in[3], DM, DM, 64, 64);
  map2(fn, &P.out, d_out, SEQ, DM, 64, 64);
  P.x_ptr = (const __nv_bfloat16*)d_in[0];
  P.wqkv_ptr = (const __nv_bfloat16*)d_in[1];
  P.wphi = (const __nv_bfloat16*)d_in[2];
  P.wo_ptr = (const __nv_bfloat16*)d_in[3];
  P.win_ptr = (const __nv_bfloat16*)d_in[5];
  P.wsp_ptr = (const __nv_bfloat16*)d_in[6];
  P.bsp = (const __nv_bfloat16*)d_in[7];
  P.wout_ptr = (const __nv_bfloat16*)d_in[8];
  P.gatew = (const __nv_bfloat16*)d_in[9];
  fused_kernel<<<128, NTHREADS, SMEM_BYTES, cudaStreamPerThread>>>(P);
}
```

```cpp
#include <cuda_runtime.h>
#include <cuda_bf16.h>
#include <cuda.h>
#include <stdint.h>

namespace hk {

constexpr int SEQ = 2048, DM = 448, FH = 896;
constexpr int NTHREADS = 640;
constexpr int OFF_X = 0, OFF_W = 7 * 16384, NW = 4, WSLOT = 16384;
constexpr int NSLOT = 5, SLOT = 32768;
constexpr int OFF_SPARE = NSLOT * SLOT;
constexpr int OFF_SC = OFF_W + NW * WSLOT;
constexpr int OFF_BAR = OFF_SC + 49152;
constexpr int SMEM_BYTES = OFF_BAR + 1024 + 1024;

constexpr int SC_WPHI = 0;
constexpr int SC_ZSTG = 8192;
constexpr int SC_KVS = 8192;
constexpr int SC_KVB = 16384;
constexpr int SC_KVF = 32768;
constexpr int SC_OSTG = 32768;
constexpr int SC_U1 = 0;
constexpr int SC_APART = 16384;
constexpr int SC_RELAY = 8192;

constexpr int BAR_XFULL = 0, BAR_WFULLB = 64, BAR_WFULLA = 96, BAR_WEMPTY = 128, BAR_FULLB = 160, BAR_FULLA = 200, BAR_EMPTY = 240;
constexpr int BAR_ZFREE = 280, BAR_ZRDY = 288, BAR_URDY = 304, BAR_ORDY = 320, BAR_KDRDY = 336, BAR_KVF = 352, BAR_SCFREE = 360;
constexpr int BAR_ZEROD = 56;
constexpr int BAR_OALL = 368, BAR_UALL = 376;
constexpr int BAR_RELRDY = 384, BAR_RELDONE = 392, BAR_GRDY = 400, BAR_REL2RDY = 408, BAR_U0RDY = 416;
constexpr int OFF_GATE = 512;
#define PF1B_AT 6
#define DEFER_GELU 1
#define PF2_MODE 0
#define NO_PF2

struct Params {
  const __nv_bfloat16 *x_ptr, *win_ptr, *wqkv_ptr, *wsp_ptr, *wout_ptr, *wo_ptr, *wphi, *bsp, *gatew;
  __nv_bfloat16* pad_[7];
  CUtensorMap x, win, wq3, wq, wz, ost, wsp, zt, ust, uld, old, wout, wo, out;
};

__device__ __align__(1024) __nv_bfloat16 g_ZT[FH * SEQ];
__device__ __align__(1024) __nv_bfloat16 g_U[SEQ * 1024];
__device__ __align__(1024) __nv_bfloat16 g_O[SEQ * 512];
__device__ __align__(1024) __nv_bfloat16 g_Wz[8 * DM * 128];
__device__ __align__(1024) __nv_bfloat16 g_Wq[16 * DM * 64];
__device__ __align__(1024) float g_KV[8 * 3584];
__device__ __align__(1024) uint2 g_stats[16 * 8 * 128];
__device__ __align__(1024) float g_gate[SEQ];
__device__ __align__(1024) unsigned g_sync[26 * 32];
__device__ __forceinline__ uint32_t clk32() { uint32_t c; asm volatile("mov.u32 %0, %%clock;" : "=r"(c)); return c; }
#define TSTAMP(role, idx) do { } while (0)
#define TP(off)

__device__ __forceinline__ uint32_t smem_u32(const void* p) { return (uint32_t)__cvta_generic_to_shared(p); }
__device__ __forceinline__ void mbar_init(uint32_t bar, uint32_t cnt) { asm volatile("mbarrier.init.shared::cta.b64 [%0], %1;" ::"r"(bar), "r"(cnt)); }
__device__ __forceinline__ void mbar_expect_tx(uint32_t bar, uint32_t bytes) { asm volatile("mbarrier.arrive.expect_tx.shared::cta.b64 _, [%0], %1;" ::"r"(bar), "r"(bytes) : "memory"); }
__device__ __forceinline__ void mbar_arrive(uint32_t bar) { asm volatile("mbarrier.arrive.shared::cta.b64 _, [%0];" ::"r"(bar) : "memory"); }
__device__ __forceinline__ bool mbar_try(uint32_t bar, uint32_t parity) {
  uint32_t ok;
  asm volatile("{\n.reg .pred p;\nmbarrier.try_wait.parity.shared::cta.b64 p, [%1], %2;\nselp.u32 %0, 1, 0, p;\n}" : "=r"(ok) : "r"(bar), "r"(parity) : "memory");
  return ok != 0;
}
__device__ __forceinline__ void mbar_wait(uint32_t bar, uint32_t parity) {
  asm volatile(
      "{\n.reg .pred p;\n.reg .u32 it;\n"
      "mbarrier.try_wait.parity.shared::cta.b64 p, [%0], %1;\n"
      "@p bra MW_DONE;\n"
      "mov.u32 it, 0;\n"
      "MW_LOOP:\n"
      "mbarrier.try_wait.parity.shared::cta.b64 p, [%0], %1;\n"
      "@p bra MW_DONE;\n"
      "add.u32 it, it, 1;\n"
      "setp.lt.u32 p, it, 1048576;\n"
      "@p bra MW_LOOP;\n"
      "MW_DONE:\n}"
      ::"r"(bar), "r"(parity) : "memory");
}
__device__ __forceinline__ void mbar_wait_u(uint32_t bar, uint32_t parity) {
  asm volatile(
      "{\n.reg .pred p;\n.reg .u32 it;\n"
      "mbarrier.try_wait.parity.shared::cta.b64 p, [%0], %1;\n"
      "@p bra.uni MW_DONE;\n"
      "mov.u32 it, 0;\n"
      "MW_LOOP:\n"
      "mbarrier.try_wait.parity.shared::cta.b64 p, [%0], %1;\n"
      "@p bra.uni MW_DONE;\n"
      "add.u32 it, it, 1;\n"
      "setp.lt.u32 p, it, 1048576;\n"
      "@p bra.uni MW_LOOP;\n"
      "MW_DONE:\n}"
      ::"r"(bar), "r"(parity) : "memory");
}
__device__ __forceinline__ bool elect_one() {
  uint32_t p;
  asm volatile("{\n.reg .pred P;\nelect.sync _|P, 0xffffffff;\nselp.u32 %0, 1, 0, P;\n}" : "=r"(p));
  return p != 0;
}
__device__ __forceinline__ void tma_ld2(uint32_t dst, const CUtensorMap* m, uint32_t bar, int c0, int c1) {
  asm volatile("cp.async.bulk.tensor.2d.shared::cluster.global.mbarrier::complete_tx::bytes [%0], [%1, {%3, %4}], [%2];"
               ::"r"(dst), "l"(m), "r"(bar), "r"(c0), "r"(c1) : "memory");
}
__device__ __forceinline__ void tma_ld3(uint32_t dst, const CUtensorMap* m, uint32_t bar, int c0, int c1, int c2) {
  asm volatile("cp.async.bulk.tensor.3d.shared::cluster.global.mbarrier::complete_tx::bytes [%0], [%1, {%3, %4, %5}], [%2];"
               ::"r"(dst), "l"(m), "r"(bar), "r"(c0), "r"(c1), "r"(c2) : "memory");
}
__device__ __forceinline__ void tma_st2(const CUtensorMap* m, uint32_t src, int c0, int c1) {
  asm volatile("cp.async.bulk.tensor.2d.global.shared::cta.bulk_group [%0, {%2, %3}], [%1];" ::"l"(m), "r"(src), "r"(c0), "r"(c1) : "memory");
}
__device__ __forceinline__ void tma_st3(const CUtensorMap* m, uint32_t src, int c0, int c1, int c2) {
  asm volatile("cp.async.bulk.tensor.3d.global.shared::cta.bulk_group [%0, {%2, %3, %4}], [%1];" ::"l"(m), "r"(src), "r"(c0), "r"(c1), "r"(c2) : "memory");
}
__device__ __forceinline__ void cp_async16(uint32_t dst, const void* src, uint32_t bytes) {
  asm volatile("cp.async.cg.shared.global [%0], [%1], 16, %2;" ::"r"(dst), "l"(src), "r"(bytes) : "memory");
}
__device__ __forceinline__ void cp_async_arrive(uint32_t bar) { asm volatile("cp.async.mbarrier.arrive.noinc.shared::cta.b64 [%0];" ::"r"(bar) : "memory"); }
__device__ __forceinline__ void bulk_commit() { asm volatile("cp.async.bulk.commit_group;" ::: "memory"); }
__device__ __forceinline__ void bulk_wait_all() { asm volatile("cp.async.bulk.wait_group 0;" ::: "memory"); }
__device__ __forceinline__ void bulk_wait_read() { asm volatile("cp.async.bulk.wait_group.read 0;" ::: "memory"); }
__device__ __forceinline__ void prefetch_map(const CUtensorMap* m) { asm volatile("prefetch.tensormap [%0];" ::"l"(m) : "memory"); }
__device__ __forceinline__ void fence_async_smem() { asm volatile("fence.proxy.async.shared::cta;" ::: "memory"); }
__device__ __forceinline__ void fence_async_global() { asm volatile("fence.proxy.async.global;" ::: "memory"); }
__device__ __forceinline__ void bar_sync(int id, int n) { asm volatile("bar.sync %0, %1;" ::"r"(id), "r"(n) : "memory"); }
__device__ __forceinline__ void bar_arrive(int id, int n) { asm volatile("bar.arrive %0, %1;" ::"r"(id), "r"(n) : "memory"); }
__device__ __forceinline__ void wg_fence() { asm volatile("wgmma.fence.sync.aligned;" ::: "memory"); }
__device__ __forceinline__ void wg_commit() { asm volatile("wgmma.commit_group.sync.aligned;" ::: "memory"); }
template <int N> __device__ __forceinline__ void wg_wait() { asm volatile("wgmma.wait_group.sync.aligned %0;" ::"n"(N) : "memory"); }
template <int N> __device__ __forceinline__ void reg_fence(float* d) {
#pragma unroll
  for (int i = 0; i < N; i++) asm volatile("" : "+f"(d[i])::"memory");
}
__device__ __forceinline__ uint64_t desc_k(uint32_t addr) { return (uint64_t)((addr & 0x3FFFF) >> 4) | (1ull << 16) | (64ull << 32) | (1ull << 62); }
__device__ __forceinline__ uint64_t desc_mn(uint32_t addr) { return (uint64_t)((addr & 0x3FFFF) >> 4) | (512ull << 16) | (64ull << 32) | (1ull << 62); }

__device__ __forceinline__ void red_release(unsigned* p) { asm volatile("red.release.gpu.global.add.u32 [%0], 1;" ::"l"(p) : "memory"); }
__device__ __forceinline__ unsigned ld_acquire(const unsigned* p) {
  unsigned v;
  asm volatile("ld.acquire.gpu.global.u32 %0, [%1];" : "=r"(v) : "l"(p) : "memory");
  return v;
}
__device__ __forceinline__ unsigned ld_relaxed(const unsigned* p) {
  unsigned v;
  asm volatile("ld.relaxed.gpu.global.u32 %0, [%1];" : "=r"(v) : "l"(p) : "memory");
  return v;
}
__device__ __forceinline__ void poll_ge(const unsigned* p, unsigned target) {
  uint32_t it = 0;
  while ((int)(ld_acquire(p) - target) < 0) { if (++it > (1u << 20)) break; }
}
__device__ __forceinline__ void red_relaxed(unsigned* p) { asm volatile("red.relaxed.gpu.global.add.u32 [%0], 1;" ::"l"(p) : "memory"); }
__device__ __forceinline__ void bulk_st(void* dst, uint32_t src, uint32_t bytes) {
  asm volatile("cp.async.bulk.global.shared::cta.bulk_group [%0], [%1], %2;" ::"l"(dst), "r"(src), "r"(bytes) : "memory");
}
__device__ __forceinline__ void bulk_reduce_f32(void* dst, uint32_t src, uint32_t bytes) {
  asm volatile("cp.reduce.async.bulk.global.shared::cta.bulk_group.add.f32 [%0], [%1], %2;" ::"l"(dst), "r"(src), "r"(bytes) : "memory");
}
__device__ __forceinline__ unsigned ld_epoch(const unsigned* p) {
  unsigned v;
  asm volatile("ld.global.cg.u32 %0, [%1];" : "=r"(v) : "l"(p));
  return v;
}
__device__ __forceinline__ void l2_prefetch(const void* p, uint32_t bytes) { asm volatile("cp.async.bulk.prefetch.L2.global [%0], %1;" ::"l"(p), "r"(bytes) : "memory"); }
__device__ __forceinline__ void prefetch_l2(const void* p) { asm volatile("prefetch.global.L2 [%0];" ::"l"(p)); }
__device__ __forceinline__ void bulk_ld(uint32_t dst, const void* src, uint32_t bytes, uint32_t bar) {
  asm volatile("cp.async.bulk.shared::cluster.global.mbarrier::complete_tx::bytes [%0], [%1], %2, [%3];" ::"r"(dst), "l"(src), "r"(bytes), "r"(bar) : "memory");
}
__device__ __forceinline__ uint2 ld_relaxed2(const uint2* p) {
  uint2 v;
  asm volatile("ld.relaxed.gpu.global.v2.u32 {%0, %1}, [%2];" : "=r"(v.x), "=r"(v.y) : "l"(p) : "memory");
  return v;
}
__device__ __forceinline__ void st_relaxed2(uint2* p, uint2 v) {
  asm volatile("st.relaxed.gpu.global.v2.u32 [%0], {%1, %2};" ::"l"(p), "r"(v.x), "r"(v.y) : "memory");
}
__device__ __forceinline__ uint4 ld_relaxed4(const uint4* p) {
  uint4 v;
  asm volatile("ld.relaxed.gpu.global.v4.u32 {%0, %1, %2, %3}, [%4];" : "=r"(v.x), "=r"(v.y), "=r"(v.z), "=r"(v.w) : "l"(p) : "memory");
  return v;
}
__device__ __forceinline__ void st_relaxed4(uint4* p, uint4 v) {
  asm volatile("st.relaxed.gpu.global.v4.u32 [%0], {%1, %2, %3, %4};" ::"l"(p), "r"(v.x), "r"(v.y), "r"(v.z), "r"(v.w) : "memory");
}
__device__ __forceinline__ uint32_t pack2(float lo, float hi) {
  uint32_t r;
  asm("cvt.rn.bf16x2.f32 %0, %1, %2;" : "=r"(r) : "f"(hi), "f"(lo));
  return r;
}
__device__ __forceinline__ float ex2f(float x) { float y; asm("ex2.approx.ftz.f32 %0, %1;" : "=f"(y) : "f"(x)); return y; }
__device__ __forceinline__ float rcpf(float x) { float y; asm("rcp.approx.ftz.f32 %0, %1;" : "=f"(y) : "f"(x)); return y; }
__device__ __forceinline__ float gelu2_f(float x) {
  const float c0 = 0.7978845608028654f, c1 = 0.7978845608028654f * 0.044715f;
  float p = fmaf(x * x, c1, c0);
  float t;
  asm("tanh.approx.f32 %0, %1;" : "=f"(t) : "f"(x * p));
  return fmaf(x, t, x);
}
__device__ __forceinline__ uint32_t gelu2_pack(uint32_t p) {
  uint32_t r;
  asm("cvt.rn.bf16x2.f32 %0, %1, %2;" : "=r"(r) : "f"(gelu2_f(__uint_as_float(p & 0xffff0000u))), "f"(gelu2_f(__uint_as_float(p << 16))));
  return r;
}
__device__ __forceinline__ void stsm4(uint32_t a, uint32_t r0, uint32_t r1, uint32_t r2, uint32_t r3) {
  asm volatile("stmatrix.sync.aligned.m8n8.x4.shared.b16 [%0], {%1, %2, %3, %4};" ::"r"(a), "r"(r0), "r"(r1), "r"(r2), "r"(r3) : "memory");
}
__device__ __forceinline__ void stsm2(uint32_t a, uint32_t r0, uint32_t r1) {
  asm volatile("stmatrix.sync.aligned.m8n8.x2.shared.b16 [%0], {%1, %2};" ::"r"(a), "r"(r0), "r"(r1) : "memory");
}
__device__ __forceinline__ void stsm4t(uint32_t a, uint32_t r0, uint32_t r1, uint32_t r2, uint32_t r3) {
  asm volatile("stmatrix.sync.aligned.m8n8.x4.trans.shared.b16 [%0], {%1, %2, %3, %4};" ::"r"(a), "r"(r0), "r"(r1), "r"(r2), "r"(r3) : "memory");
}
__device__ __forceinline__ float qmax(float v) { v = fmaxf(v, __shfl_xor_sync(~0u, v, 1)); return fmaxf(v, __shfl_xor_sync(~0u, v, 2)); }
__device__ __forceinline__ float qmin(float v) { v = fminf(v, __shfl_xor_sync(~0u, v, 1)); return fminf(v, __shfl_xor_sync(~0u, v, 2)); }
__device__ __forceinline__ float qsum(float v) { v += __shfl_xor_sync(~0u, v, 1); return v + __shfl_xor_sync(~0u, v, 2); }

__device__ __forceinline__ void wgmma_ss_n112_t01(float* d, uint64_t da, uint64_t db, int scale_d) {
  asm volatile("{\n.reg .pred p;\nsetp.ne.b32 p, %58, 0;\n"
    "wgmma.mma_async.sync.aligned.m64n112k16.f32.bf16.bf16 "
    "{%0, %1, %2, %3, %4, %5, %6, %7, %8, %9, %10, %11, %12, %13, %14, %15, %16, %17, %18, %19, %20, %21, %22, %23, %24, %25, %26, %27, %28, %29, %30, %31, %32, %33, %34, %35, %36, %37, %38, %39, %40, %41, %42, %43, %44, %45, %46, %47, %48, %49, %50, %51, %52, %53, %54, %55}, "
    "%56, %57, p, 1, 1, 0, 1;\n}"
    : "+f"(d[0]), "+f"(d[1]), "+f"(d[2]), "+f"(d[3]), "+f"(d[4]), "+f"(d[5]), "+f"(d[6]), "+f"(d[7]), "+f"(d[8]), "+f"(d[9]), "+f"(d[10]), "+f"(d[11]), "+f"(d[12]), "+f"(d[13]), "+f"(d[14]), "+f"(d[15]), "+f"(d[16]), "+f"(d[17]), "+f"(d[18]), "+f"(d[19]), "+f"(d[20]), "+f"(d[21]), "+f"(d[22]), "+f"(d[23]), "+f"(d[24]), "+f"(d[25]), "+f"(d[26]), "+f"(d[27]), "+f"(d[28]), "+f"(d[29]), "+f"(d[30]), "+f"(d[31]), "+f"(d[32]), "+f"(d[33]), "+f"(d[34]), "+f"(d[35]), "+f"(d[36]), "+f"(d[37]), "+f"(d[38]), "+f"(d[39]), "+f"(d[40]), "+f"(d[41]), "+f"(d[42]), "+f"(d[43]), "+f"(d[44]), "+f"(d[45]), "+f"(d[46]), "+f"(d[47]), "+f"(d[48]), "+f"(d[49]), "+f"(d[50]), "+f"(d[51]), "+f"(d[52]), "+f"(d[53]), "+f"(d[54]), "+f"(d[55])
    : "l"(da), "l"(db), "r"(scale_d));
}
__device__ __forceinline__ void wgmma_ss_n112_t00(float* d, uint64_t da, uint64_t db, int scale_d) {
  asm volatile("{\n.reg .pred p;\nsetp.ne.b32 p, %58, 0;\n"
    "wgmma.mma_async.sync.aligned.m64n112k16.f32.bf16.bf16 "
    "{%0, %1, %2, %3, %4, %5, %6, %7, %8, %9, %10, %11, %12, %13, %14, %15, %16, %17, %18, %19, %20, %21, %22, %23, %24, %25, %26, %27, %28, %29, %30, %31, %32, %33, %34, %35, %36, %37, %38, %39, %40, %41, %42, %43, %44, %45, %46, %47, %48, %49, %50, %51, %52, %53, %54, %55}, "
    "%56, %57, p, 1, 1, 0, 0;\n}"
    : "+f"(d[0]), "+f"(d[1]), "+f"(d[2]), "+f"(d[3]), "+f"(d[4]), "+f"(d[5]), "+f"(d[6]), "+f"(d[7]), "+f"(d[8]), "+f"(d[9]), "+f"(d[10]), "+f"(d[11]), "+f"(d[12]), "+f"(d[13]), "+f"(d[14]), "+f"(d[15]), "+f"(d[16]), "+f"(d[17]), "+f"(d[18]), "+f"(d[19]), "+f"(d[20]), "+f"(d[21]), "+f"(d[22]), "+f"(d[23]), "+f"(d[24]), "+f"(d[25]), "+f"(d[26]), "+f"(d[27]), "+f"(d[28]), "+f"(d[29]), "+f"(d[30]), "+f"(d[31]), "+f"(d[32]), "+f"(d[33]), "+f"(d[34]), "+f"(d[35]), "+f"(d[36]), "+f"(d[37]), "+f"(d[38]), "+f"(d[39]), "+f"(d[40]), "+f"(d[41]), "+f"(d[42]), "+f"(d[43]), "+f"(d[44]), "+f"(d[45]), "+f"(d[46]), "+f"(d[47]), "+f"(d[48]), "+f"(d[49]), "+f"(d[50]), "+f"(d[51]), "+f"(d[52]), "+f"(d[53]), "+f"(d[54]), "+f"(d[55])
    : "l"(da), "l"(db), "r"(scale_d));
}
__device__ __forceinline__ void wgmma_ss_n128_t01(float* d, uint64_t da, uint64_t db, int scale_d) {
  asm volatile("{\n.reg .pred p;\nsetp.ne.b32 p, %66, 0;\n"
    "wgmma.mma_async.sync.aligned.m64n128k16.f32.bf16.bf16 "
    "{%0, %1, %2, %3, %4, %5, %6, %7, %8, %9, %10, %11, %12, %13, %14, %15, %16, %17, %18, %19, %20, %21, %22, %23, %24, %25, %26, %27, %28, %29, %30, %31, %32, %33, %34, %35, %36, %37, %38, %39, %40, %41, %42, %43, %44, %45, %46, %47, %48, %49, %50, %51, %52, %53, %54, %55, %56, %57, %58, %59, %60, %61, %62, %63}, "
    "%64, %65, p, 1, 1, 0, 1;\n}"
    : "+f"(d[0]), "+f"(d[1]), "+f"(d[2]), "+f"(d[3]), "+f"(d[4]), "+f"(d[5]), "+f"(d[6]), "+f"(d[7]), "+f"(d[8]), "+f"(d[9]), "+f"(d[10]), "+f"(d[11]), "+f"(d[12]), "+f"(d[13]), "+f"(d[14]), "+f"(d[15]), "+f"(d[16]), "+f"(d[17]), "+f"(d[18]), "+f"(d[19]), "+f"(d[20]), "+f"(d[21]), "+f"(d[22]), "+f"(d[23]), "+f"(d[24]), "+f"(d[25]), "+f"(d[26]), "+f"(d[27]), "+f"(d[28]), "+f"(d[29]), "+f"(d[30]), "+f"(d[31]), "+f"(d[32]), "+f"(d[33]), "+f"(d[34]), "+f"(d[35]), "+f"(d[36]), "+f"(d[37]), "+f"(d[38]), "+f"(d[39]), "+f"(d[40]), "+f"(d[41]), "+f"(d[42]), "+f"(d[43]), "+f"(d[44]), "+f"(d[45]), "+f"(d[46]), "+f"(d[47]), "+f"(d[48]), "+f"(d[49]), "+f"(d[50]), "+f"(d[51]), "+f"(d[52]), "+f"(d[53]), "+f"(d[54]), "+f"(d[55]), "+f"(d[56]), "+f"(d[57]), "+f"(d[58]), "+f"(d[59]), "+f"(d[60]), "+f"(d[61]), "+f"(d[62]), "+f"(d[63])
    : "l"(da), "l"(db), "r"(scale_d));
}
__device__ __forceinline__ void wgmma_ss_n56_t01(float* d, uint64_t da, uint64_t db, int scale_d) {
  asm volatile("{\n.reg .pred p;\nsetp.ne.b32 p, %30, 0;\n"
    "wgmma.mma_async.sync.aligned.m64n56k16.f32.bf16.bf16 "
    "{%0, %1, %2, %3, %4, %5, %6, %7, %8, %9, %10, %11, %12, %13, %14, %15, %16, %17, %18, %19, %20, %21, %22, %23, %24, %25, %26, %27}, "
    "%28, %29, p, 1, 1, 0, 1;\n}"
    : "+f"(d[0]), "+f"(d[1]), "+f"(d[2]), "+f"(d[3]), "+f"(d[4]), "+f"(d[5]), "+f"(d[6]), "+f"(d[7]), "+f"(d[8]), "+f"(d[9]), "+f"(d[10]), "+f"(d[11]), "+f"(d[12]), "+f"(d[13]), "+f"(d[14]), "+f"(d[15]), "+f"(d[16]), "+f"(d[17]), "+f"(d[18]), "+f"(d[19]), "+f"(d[20]), "+f"(d[21]), "+f"(d[22]), "+f"(d[23]), "+f"(d[24]), "+f"(d[25]), "+f"(d[26]), "+f"(d[27])
    : "l"(da), "l"(db), "r"(scale_d));
}
__device__ __forceinline__ void wgmma_ss_n64_t11(float* d, uint64_t da, uint64_t db, int scale_d) {
  asm volatile("{\n.reg .pred p;\nsetp.ne.b32 p, %34, 0;\n"
    "wgmma.mma_async.sync.aligned.m64n64k16.f32.bf16.bf16 "
    "{%0, %1, %2, %3, %4, %5, %6, %7, %8, %9, %10, %11, %12, %13, %14, %15, %16, %17, %18, %19, %20, %21, %22, %23, %24, %25, %26, %27, %28, %29, %30, %31}, "
    "%32, %33, p, 1, 1, 1, 1;\n}"
    : "+f"(d[0]), "+f"(d[1]), "+f"(d[2]), "+f"(d[3]), "+f"(d[4]), "+f"(d[5]), "+f"(d[6]), "+f"(d[7]), "+f"(d[8]), "+f"(d[9]), "+f"(d[10]), "+f"(d[11]), "+f"(d[12]), "+f"(d[13]), "+f"(d[14]), "+f"(d[15]), "+f"(d[16]), "+f"(d[17]), "+f"(d[18]), "+f"(d[19]), "+f"(d[20]), "+f"(d[21]), "+f"(d[22]), "+f"(d[23]), "+f"(d[24]), "+f"(d[25]), "+f"(d[26]), "+f"(d[27]), "+f"(d[28]), "+f"(d[29]), "+f"(d[30]), "+f"(d[31])
    : "l"(da), "l"(db), "r"(scale_d));
}
__device__ __forceinline__ void wgmma_ss_n64_t01(float* d, uint64_t da, uint64_t db, int scale_d) {
  asm volatile("{\n.reg .pred p;\nsetp.ne.b32 p, %34, 0;\n"
    "wgmma.mma_async.sync.aligned.m64n64k16.f32.bf16.bf16 "
    "{%0, %1, %2, %3, %4, %5, %6, %7, %8, %9, %10, %11, %12, %13, %14, %15, %16, %17, %18, %19, %20, %21, %22, %23, %24, %25, %26, %27, %28, %29, %30, %31}, "
    "%32, %33, p, 1, 1, 0, 1;\n}"
    : "+f"(d[0]), "+f"(d[1]), "+f"(d[2]), "+f"(d[3]), "+f"(d[4]), "+f"(d[5]), "+f"(d[6]), "+f"(d[7]), "+f"(d[8]), "+f"(d[9]), "+f"(d[10]), "+f"(d[11]), "+f"(d[12]), "+f"(d[13]), "+f"(d[14]), "+f"(d[15]), "+f"(d[16]), "+f"(d[17]), "+f"(d[18]), "+f"(d[19]), "+f"(d[20]), "+f"(d[21]), "+f"(d[22]), "+f"(d[23]), "+f"(d[24]), "+f"(d[25]), "+f"(d[26]), "+f"(d[27]), "+f"(d[28]), "+f"(d[29]), "+f"(d[30]), "+f"(d[31])
    : "l"(da), "l"(db), "r"(scale_d));
}
__device__ __forceinline__ void wgmma_rs_n56_t1(float* d, uint32_t a0, uint32_t a1, uint32_t a2, uint32_t a3, uint64_t db, int scale_d) {
  asm volatile("{\n.reg .pred p;\nsetp.ne.b32 p, %33, 0;\n"
    "wgmma.mma_async.sync.aligned.m64n56k16.f32.bf16.bf16 "
    "{%0, %1, %2, %3, %4, %5, %6, %7, %8, %9, %10, %11, %12, %13, %14, %15, %16, %17, %18, %19, %20, %21, %22, %23, %24, %25, %26, %27}, "
    "{%28, %29, %30, %31}, %32, p, 1, 1, 1;\n}"
    : "+f"(d[0]), "+f"(d[1]), "+f"(d[2]), "+f"(d[3]), "+f"(d[4]), "+f"(d[5]), "+f"(d[6]), "+f"(d[7]), "+f"(d[8]), "+f"(d[9]), "+f"(d[10]), "+f"(d[11]), "+f"(d[12]), "+f"(d[13]), "+f"(d[14]), "+f"(d[15]), "+f"(d[16]), "+f"(d[17]), "+f"(d[18]), "+f"(d[19]), "+f"(d[20]), "+f"(d[21]), "+f"(d[22]), "+f"(d[23]), "+f"(d[24]), "+f"(d[25]), "+f"(d[26]), "+f"(d[27])
    : "r"(a0), "r"(a1), "r"(a2), "r"(a3), "l"(db), "r"(scale_d));
}
__device__ __forceinline__ void wgmma_rs_n64_t1(float* d, uint32_t a0, uint32_t a1, uint32_t a2, uint32_t a3, uint64_t db, int scale_d) {
  asm volatile("{\n.reg .pred p;\nsetp.ne.b32 p, %37, 0;\n"
    "wgmma.mma_async.sync.aligned.m64n64k16.f32.bf16.bf16 "
    "{%0, %1, %2, %3, %4, %5, %6, %7, %8, %9, %10, %11, %12, %13, %14, %15, %16, %17, %18, %19, %20, %21, %22, %23, %24, %25, %26, %27, %28, %29, %30, %31}, "
    "{%32, %33, %34, %35}, %36, p, 1, 1, 1;\n}"
    : "+f"(d[0]), "+f"(d[1]), "+f"(d[2]), "+f"(d[3]), "+f"(d[4]), "+f"(d[5]), "+f"(d[6]), "+f"(d[7]), "+f"(d[8]), "+f"(d[9]), "+f"(d[10]), "+f"(d[11]), "+f"(d[12]), "+f"(d[13]), "+f"(d[14]), "+f"(d[15]), "+f"(d[16]), "+f"(d[17]), "+f"(d[18]), "+f"(d[19]), "+f"(d[20]), "+f"(d[21]), "+f"(d[22]), "+f"(d[23]), "+f"(d[24]), "+f"(d[25]), "+f"(d[26]), "+f"(d[27]), "+f"(d[28]), "+f"(d[29]), "+f"(d[30]), "+f"(d[31])
    : "r"(a0), "r"(a1), "r"(a2), "r"(a3), "l"(db), "r"(scale_d));
}
__device__ __forceinline__ void wgmma_ss_n120_t01(float* d, uint64_t da, uint64_t db, int scale_d) {
  asm volatile("{\n.reg .pred p;\nsetp.ne.b32 p, %62, 0;\n"
    "wgmma.mma_async.sync.aligned.m64n120k16.f32.bf16.bf16 "
    "{%0, %1, %2, %3, %4, %5, %6, %7, %8, %9, %10, %11, %12, %13, %14, %15, %16, %17, %18, %19, %20, %21, %22, %23, %24, %25, %26, %27, %28, %29, %30, %31, %32, %33, %34, %35, %36, %37, %38, %39, %40, %41, %42, %43, %44, %45, %46, %47, %48, %49, %50, %51, %52, %53, %54, %55, %56, %57, %58, %59}, "
    "%60, %61, p, 1, 1, 0, 1;\n}"
    : "+f"(d[0]), "+f"(d[1]), "+f"(d[2]), "+f"(d[3]), "+f"(d[4]), "+f"(d[5]), "+f"(d[6]), "+f"(d[7]), "+f"(d[8]), "+f"(d[9]), "+f"(d[10]), "+f"(d[11]), "+f"(d[12]), "+f"(d[13]), "+f"(d[14]), "+f"(d[15]), "+f"(d[16]), "+f"(d[17]), "+f"(d[18]), "+f"(d[19]), "+f"(d[20]), "+f"(d[21]), "+f"(d[22]), "+f"(d[23]), "+f"(d[24]), "+f"(d[25]), "+f"(d[26]), "+f"(d[27]), "+f"(d[28]), "+f"(d[29]), "+f"(d[30]), "+f"(d[31]), "+f"(d[32]), "+f"(d[33]), "+f"(d[34]), "+f"(d[35]), "+f"(d[36]), "+f"(d[37]), "+f"(d[38]), "+f"(d[39]), "+f"(d[40]), "+f"(d[41]), "+f"(d[42]), "+f"(d[43]), "+f"(d[44]), "+f"(d[45]), "+f"(d[46]), "+f"(d[47]), "+f"(d[48]), "+f"(d[49]), "+f"(d[50]), "+f"(d[51]), "+f"(d[52]), "+f"(d[53]), "+f"(d[54]), "+f"(d[55]), "+f"(d[56]), "+f"(d[57]), "+f"(d[58]), "+f"(d[59])
    : "l"(da), "l"(db), "r"(scale_d));
}

template <int V> struct IC { static constexpr int value = V; };
struct NoHook { template <class T> __device__ __forceinline__ void operator()(T) const {} };
template <int I, int N, class F> __device__ __forceinline__ void for_range(F&& f) {
  if constexpr (I < N) { f(IC<I>()); for_range<I + 1, N>(f); }
}
template <int N, int I = 0, class F> __device__ __forceinline__ void static_for(F&& f) {
  if constexpr (I < N) { f(IC<I>()); static_for<N, I + 1>(f); }
}

__host__ __device__ constexpr bool w_team_b(int n) { return n < 7 || n == 17 || n >= 19; }
__host__ __device__ constexpr int w_seq(int n0, int s) {
  return n0 == 11 ? (s < 6 ? 11 + s : 18) : (n0 == 17 ? (s == 0 ? 17 : 18 + s) : n0 + s);
}
__host__ __device__ constexpr int w_par(int n) {
  int c = 0;
  for (int m = n & 3; m < n; m += NW) c += (w_team_b(m) == w_team_b(n));
  return c & 1;
}
__host__ __device__ constexpr bool r_team_b(int n) { return n < 32 || n >= 40; }
__host__ __device__ constexpr int r_par(int n) {
  int c = 0;
  for (int m = n % NSLOT; m < n; m += NSLOT) c += (r_team_b(m) == r_team_b(n));
  return c & 1;
}
__device__ __forceinline__ uint64_t desc_k_lo(uint32_t lo) { return (uint64_t)lo | (0x40000040ull << 32); }
__device__ __forceinline__ uint64_t launder(uint64_t x) { uint64_t y; asm("mov.b64 %0, %1;" : "=l"(y) : "l"(x)); return y; }
#define TP_PARAMS
#define TP_STAMP(s) do { } while (0)

template <int KIND, int N0, bool WAITX, class Hook>
__device__ __forceinline__ void consume1(float* acc, uint32_t sbase, int w, int lane, Hook hook TP_PARAMS) {
  const uint32_t bars = sbase + OFF_BAR;
  const uint32_t ax0 = ((sbase + OFF_X + w * 8192) >> 4) | 0x10000u;
  const uint64_t dw = launder(desc_mn(sbase + OFF_W));
  static_for<7>([&](auto si) {
    constexpr int s = decltype(si)::value, n = w_seq(N0, s), slot = n & (NW - 1);
    if (WAITX) mbar_wait_u(bars + BAR_XFULL + 8 * s, 0);
    mbar_wait_u(bars + (w_team_b(n) ? BAR_WFULLB : BAR_WFULLA) + 8 * slot, w_par(n));
    TP_STAMP(s);
    uint32_t ax = ax0;
    asm volatile("" : "+r"(ax));
    wg_fence();
#pragma unroll
    for (int k = 0; k < 4; k++) {
      if (KIND == 0) wgmma_ss_n112_t01(acc, desc_k_lo(ax + s * 1024 + 2 * k), dw + (slot * 1024 + 128 * k), (s | k) != 0);
      if (KIND == 2) wgmma_ss_n128_t01(acc, desc_k_lo(ax + s * 1024 + 2 * k), dw + (slot * 1024 + 128 * k), (s | k) != 0);
    }
    wg_commit();
    hook(si);
    if constexpr (s > 0) {
      wg_wait<1>();
      if (lane == 0) mbar_arrive(bars + BAR_WEMPTY + 8 * (w_seq(N0, s - 1) & (NW - 1)));
    }
  });
  wg_wait<0>();
  if (lane == 0) mbar_arrive(bars + BAR_WEMPTY + 8 * (w_seq(N0, 6) & (NW - 1)));
}
__device__ __forceinline__ void consume_q(float* acc, uint32_t sbase, int w, int lane TP_PARAMS) {
  const uint32_t bars = sbase + OFF_BAR;
  const uint32_t ax0 = ((sbase + OFF_X + w * 8192) >> 4) | 0x10000u;
  const uint64_t dw = launder(desc_mn(sbase + OFF_W));
  static_for<4>([&](auto si) {
    constexpr int s = decltype(si)::value, n = w_seq(7, s), slot = n & (NW - 1);
    if (s == 0) for (int m = 0; m < 7; m++) mbar_wait_u(bars + BAR_XFULL + 8 * m, 0);
    mbar_wait_u(bars + BAR_WFULLA + 8 * slot, w_par(n));
    TP_STAMP(s);
    uint32_t ax = ax0;
    asm volatile("" : "+r"(ax));
    wg_fence();
#pragma unroll
    for (int k = 0; k < 4; k++) wgmma_ss_n56_t01(acc, desc_k_lo(ax + 2 * s * 1024 + 2 * k), dw + (slot * 1024 + 128 * k), (s | k) != 0);
    if constexpr (s < 3) {
#pragma unroll
      for (int k = 0; k < 4; k++) wgmma_ss_n56_t01(acc, desc_k_lo(ax + (2 * s + 1) * 1024 + 2 * k), dw + (slot * 1024 + 512 + 128 * k), 1);
    }
    wg_commit();
    if constexpr (s > 0) {
      wg_wait<1>();
      if (lane == 0) mbar_arrive(bars + BAR_WEMPTY + 8 * (w_seq(7, s - 1) & (NW - 1)));
    }
  });
  wg_wait<0>();
  if (lane == 0) mbar_arrive(bars + BAR_WEMPTY + 8 * (w_seq(7, 3) & (NW - 1)));
}

template <int MODE, class Hook>
__device__ __forceinline__ void consume2(float* acc, uint32_t sbase, int w, int lane, Hook hook TP_PARAMS) {
  constexpr int N0 = MODE == 0 ? 0 : (MODE == 1 ? 32 : 40), NST = MODE == 0 ? 32 : (MODE == 1 ? 8 : 16);
  const uint32_t bars = sbase + OFF_BAR;
  const uint32_t ax0 = ((sbase + w * 8192) >> 4) | 0x10000u;
  const uint64_t db = launder(MODE == 0 ? desc_k(sbase + 16384) : desc_mn(sbase + 16384));
  auto stage = [&](auto si, uint32_t par, int sreal) {
    constexpr int s = decltype(si)::value, n = N0 + s, slot = n % NSLOT;
    mbar_wait_u(bars + (r_team_b(n) ? BAR_FULLB : BAR_FULLA) + 8 * slot, par);
    TP_STAMP(sreal);
    constexpr int aoff = (MODE == 2 && s == 0) ? OFF_SPARE / 16 : ((MODE == 2 && s == 1) ? (OFF_SC + SC_U1) / 16 : slot * (SLOT / 16));
    constexpr int boff = slot * (SLOT / 16), nk = (MODE == 2 && (s & 1)) ? 3 : 4;
    uint32_t ax = ax0;
    asm volatile("" : "+r"(ax));
    wg_fence();
#pragma unroll
    for (int k = 0; k < nk; k++) {
      if (MODE == 0) wgmma_ss_n112_t00(acc, desc_k_lo(ax + aoff + 2 * k), db + (boff + 2 * k), (s | k) != 0);
      else wgmma_ss_n64_t01(acc, desc_k_lo(ax + aoff + 2 * k), db + (boff + 128 * k), (s | k) != 0);
    }
    wg_commit();
    if (s > 0) {
      wg_wait<1>();
      if (lane == 0) mbar_arrive(bars + BAR_EMPTY + 8 * ((n + NSLOT - 1) % NSLOT));
    }
  };
  if constexpr (MODE == 0) {
    stage(IC<0>(), 0, 0);
    stage(IC<1>(), 0, 1);
#pragma unroll 1
    for (int it = 0; it < 6; it++) {
      const uint32_t p0 = it & 1, p1 = p0 ^ 1;
      stage(IC<2>(), p0, 2 + 5 * it);
      hook(it);
      stage(IC<3>(), p0, 3 + 5 * it);
      stage(IC<4>(), p0, 4 + 5 * it);
      stage(IC<5>(), p1, 5 + 5 * it);
      stage(IC<6>(), p1, 6 + 5 * it);
    }
  } else {
    static_for<NST>([&](auto si) { stage(si, r_par(N0 + decltype(si)::value), decltype(si)::value); });
  }
  wg_wait<0>();
  if (lane == 0) mbar_arrive(bars + BAR_EMPTY + 8 * ((N0 + NST - 1) % NSLOT));
}

__device__ __forceinline__ void feature_map(const float* p, uint32_t* out, int q) {
  const float L = 1.4426950408889634f;
  const bool lo = q < 2;
  float v[14], nx[14];
#pragma unroll
  for (int b = 0; b < 7; b++) {
    v[2 * b] = p[4 * b]; v[2 * b + 1] = p[4 * b + 1];
    nx[2 * b] = p[4 * b + 2]; nx[2 * b + 1] = p[4 * b + 3];
  }
#pragma unroll 1
  for (int r = 0; r < 2; r++) {
    float mx0 = fmaxf(fmaxf(fmaxf(v[0], v[1]), fmaxf(v[2], v[3])), fmaxf(v[4], v[5]));
    float mn0 = fminf(fminf(fminf(v[0], v[1]), fminf(v[2], v[3])), fminf(v[4], v[5]));
    float mx1 = fmaxf(fmaxf(fmaxf(v[8], v[9]), fmaxf(v[10], v[11])), fmaxf(v[12], v[13]));
    float mn1 = fminf(fminf(fminf(v[8], v[9]), fminf(v[10], v[11])), fminf(v[12], v[13]));
    const float mx3 = fmaxf(v[6], v[7]), mn3 = fminf(v[6], v[7]);
    if (lo) { mx0 = fmaxf(mx0, mx3); mn0 = fminf(mn0, mn3); } else { mx1 = fmaxf(mx1, mx3); mn1 = fminf(mn1, mn3); }
    mx0 = qmax(mx0); mx1 = qmax(mx1); mn0 = qmin(mn0); mn1 = qmin(mn1);
    const float a0 = -mx0 * L, a1 = -mx1 * L, c0 = mn0 * L, c1 = mn1 * L;
    const float a3 = lo ? a0 : a1, c3 = lo ? c0 : c1;
    float ep[14], em[14];
#pragma unroll
    for (int e = 0; e < 14; e++) {
      const float a = e < 6 ? a0 : (e < 8 ? a3 : a1), c = e < 6 ? c0 : (e < 8 ? c3 : c1);
      ep[e] = ex2f(fmaf(v[e], L, a));
      em[e] = ex2f(fmaf(v[e], -L, c));
    }
    float sp0 = ((ep[0] + ep[1]) + (ep[2] + ep[3])) + (ep[4] + ep[5]), sm0 = ((em[0] + em[1]) + (em[2] + em[3])) + (em[4] + em[5]);
    float sp1 = ((ep[8] + ep[9]) + (ep[10] + ep[11])) + (ep[12] + ep[13]), sm1 = ((em[8] + em[9]) + (em[10] + em[11])) + (em[12] + em[13]);
    const float sp3 = ep[6] + ep[7], sm3 = em[6] + em[7];
    if (lo) { sp0 += sp3; sm0 += sm3; } else { sp1 += sp3; sm1 += sm3; }
    const float rp0 = rcpf(qsum(sp0)), rp1 = rcpf(qsum(sp1)), rm0 = rcpf(qsum(sm0)), rm1 = rcpf(qsum(sm1));
    const float rp3 = lo ? rp0 : rp1, rm3 = lo ? rm0 : rm1;
#pragma unroll
    for (int b = 0; b < 7; b++) {
      const float rp = b < 3 ? rp0 : (b == 3 ? rp3 : rp1), rm = b < 3 ? rm0 : (b == 3 ? rm3 : rm1);
      ep[b] = __uint_as_float(pack2(ep[2 * b] * rp, ep[2 * b + 1] * rp));
      em[b] = __uint_as_float(pack2(em[2 * b] * rm, em[2 * b + 1] * rm));
    }
#pragma unroll
    for (int e = 0; e < 14; e++) { v[e] = nx[e]; nx[e] = e < 7 ? ep[e] : em[e - 7]; }
  }
#pragma unroll
  for (int b = 0; b < 7; b++) {
    out[2 * b] = __float_as_uint(v[b]); out[2 * b + 1] = __float_as_uint(nx[b]);
    out[14 + 2 * b] = __float_as_uint(v[7 + b]); out[14 + 2 * b + 1] = __float_as_uint(nx[7 + b]);
  }
}

template <int NB>
__device__ __forceinline__ void store_frag(uint32_t tile, int row0, const uint32_t* p, int lane) {
  const int m = lane >> 3, rr = lane & 7;
  const int row = row0 + 8 * (m & 1) + rr;
  const uint32_t ra = tile + row * 128;
#pragma unroll
  for (int b = 0; b + 1 < NB; b += 2) stsm4(ra + (((b + (m >> 1)) ^ rr) << 4), p[2 * b], p[2 * b + 1], p[2 * b + 2], p[2 * b + 3]);
  if (NB & 1) stsm2(ra + (((NB - 1) ^ rr) << 4), p[2 * (NB - 1)], p[2 * (NB - 1) + 1]);
}

__global__ void __launch_bounds__(NTHREADS, 1) fused_kernel(const __grid_constant__ Params P) {
  extern __shared__ uint8_t smem_raw[];
  const uint32_t sbase = (smem_u32(smem_raw) + 1023) & ~1023u;
  uint8_t* sgen = smem_raw + (sbase - smem_u32(smem_raw));
  const uint32_t sc = sbase + OFF_SC, bars = sbase + OFF_BAR;
  const int warp = __shfl_sync(~0u, (int)(threadIdx.x >> 5), 0), lane = threadIdx.x & 31;
  const int um = blockIdx.x >> 4, uh = ((blockIdx.x >> 3) ^ um) & 1;
  const int bi = 2 * um + ((blockIdx.x >> 2) & 1), bj = 4 * uh + (blockIdx.x & 3);
  unsigned* syncI = g_sync + bi * 32;
  unsigned* syncJ = g_sync + (16 + bj) * 32;

  if (warp >= 16) {
    asm volatile("setmaxnreg.dec.sync.aligned.u32 32;");
    auto init_range = [&](auto first) {
#pragma unroll
      for (int b = decltype(first)::value; b < decltype(first)::value + 14; b++) {
        const int off = 8 * b;
        int cnt = 1;
        if ((off >= BAR_WEMPTY && off < BAR_FULLB) || (off >= BAR_EMPTY && off < BAR_ZFREE) || off == BAR_SCFREE || off == BAR_RELRDY || off == BAR_GRDY || off == BAR_REL2RDY) cnt = 8;
        if ((off >= BAR_ZRDY && off < BAR_KVF) || off == BAR_U0RDY || off == BAR_U0RDY + 8) cnt = 4;
        mbar_init(bars + off, cnt);
      }
      asm volatile("fence.mbarrier_init.release.cluster;" ::: "memory");
    };
    if (warp == 16) {
      if (elect_one()) { prefetch_map(&P.x); prefetch_map(&P.win); init_range(IC<0>()); }
      __syncwarp();
      bar_arrive(8, NTHREADS);
      if (elect_one()) {
        TSTAMP(2, 17);
#pragma unroll
        for (int k = 0; k < 7; k++) {
          mbar_expect_tx(bars + BAR_XFULL + 8 * k, 16384);
          tma_ld2(sbase + OFF_X + k * 16384, &P.x, bars + BAR_XFULL + 8 * k, 64 * k, bi * 128);
          if (k < NW) {
            mbar_expect_tx(bars + BAR_WFULLB + 8 * k, 16384);
            tma_ld2(sbase + OFF_W + k * WSLOT, &P.win, bars + BAR_WFULLB + 8 * k, FH + 112 * bj, 64 * k);
            tma_ld2(sbase + OFF_W + k * WSLOT + 8192, &P.win, bars + BAR_WFULLB + 8 * k, FH + 112 * bj + 64, 64 * k);
          }
        }
        TSTAMP(2, 18);
      }
      __syncwarp();
      bar_sync(9, 128);
    } else {
      if (elect_one()) {
        if (warp == 17) init_range(IC<14>());
        else if (warp == 18) { init_range(IC<28>()); prefetch_map(&P.wq3); prefetch_map(&P.wq); }
        else init_range(IC<42>());
      }
      __syncwarp();
      bar_arrive(9, 128);
      bar_sync(8, NTHREADS);
    }
    if (!elect_one()) return;
    const int t0 = bi * 128;
    const unsigned epoch = ld_epoch(syncI + 8 + bj);
    if (warp == 16) {
      TSTAMP(2, 16);
#define PSTAMP() do { } while (0)
      int slot = 0;
      uint32_t eph = 0;
      auto wload = [&](const CUtensorMap* m, uint32_t full, int c0, int r0, int c1, int r1, bool two) {
        mbar_wait_u(bars + BAR_WEMPTY + 8 * slot, (eph >> slot) & 1);
        eph ^= 1u << slot;
        const uint32_t sw = sbase + OFF_W + slot * WSLOT, fb = bars + full + 8 * slot;
        mbar_expect_tx(fb, two ? 16384 : 8192);
        tma_ld2(sw, m, fb, c0, r0);
        if (two) tma_ld2(sw + 8192, m, fb, c1, r1);
        slot = (slot + 1) & (NW - 1);
        PSTAMP();
      };
#pragma unroll 1
      for (int k = NW; k < 7; k++) wload(&P.win, BAR_WFULLB, FH + 112 * bj, 64 * k, FH + 112 * bj + 64, 64 * k, true);
      TSTAMP(2, 0);
#pragma unroll 1
      for (int k = 0; k < 4; k++) {
        mbar_wait_u(bars + BAR_WEMPTY + 8 * slot, (eph >> slot) & 1);
        eph ^= 1u << slot;
        const uint32_t sw = sbase + OFF_W + slot * WSLOT, fb = bars + BAR_WFULLA + 8 * slot;
        mbar_expect_tx(fb, k < 3 ? 16384 : 8192);
        tma_ld3(sw, &P.wq3, fb, 0, bj, 128 * k);
        if (k < 3) tma_ld3(sw + 8192, &P.wq3, fb, 0, bj, 128 * k + 64);
        slot = (slot + 1) & (NW - 1);
        PSTAMP();
      }
      TSTAMP(2, 2);
      poll_ge(g_sync + 25 * 32, (epoch + 1) * 128);
      fence_async_global();
      TSTAMP(2, 12);
#pragma unroll 1
      for (int k = 0; k < 6; k++) wload(&P.wq, BAR_WFULLA, 0, bj * DM + 64 * k, 0, (8 + bj) * DM + 64 * k, true);
      TSTAMP(2, 1);
      prefetch_map(&P.wz); prefetch_map(&P.wsp); prefetch_map(&P.zt);
      poll_ge(g_sync + 25 * 32 + 1, (epoch + 1) * 128);
      fence_async_global();
      wload(&P.wz, BAR_WFULLB, 0, bj * DM, 64, bj * DM, true);
      wload(&P.wq, BAR_WFULLA, 0, bj * DM + 384, 0, (8 + bj) * DM + 384, true);
#pragma unroll 1
      for (int k = 1; k < 7; k++) wload(&P.wz, BAR_WFULLB, 0, bj * DM + 64 * k, 64, bj * DM + 64 * k, true);
      TSTAMP(2, 3);
      prefetch_map(&P.old); prefetch_map(&P.wo); prefetch_map(&P.uld); prefetch_map(&P.wout);
      unsigned* cntA = g_sync + 24 * 32;
      red_relaxed(cntA);
      poll_ge(syncJ + 0, (epoch + 1) * 16);
      int rs = 0;
      uint32_t rph = 0;
      auto rload = [&](uint32_t full, uint32_t bytes, const CUtensorMap* ma, int a0, int a1, bool with_a, const CUtensorMap* mb, int b0, int b1) {
        const uint32_t sa = sbase + rs * SLOT, fb = bars + full + 8 * rs;
        mbar_expect_tx(fb, bytes);
        if (with_a) tma_ld2(sa, ma, fb, a0, a1);
        tma_ld2(sa + 16384, mb, fb, b0, b1);
        rs = (rs == NSLOT - 1) ? 0 : rs + 1;
        PSTAMP();
      };
      auto rwait = [&]() { mbar_wait_u(bars + BAR_EMPTY + 8 * rs, (rph >> rs) & 1); rph ^= 1u << rs; };
#pragma unroll 1
      for (int k = 0; k < 32; k++) {
        if (k >= NSLOT) rwait();
        else {
          const int nd = k == 0 ? 1 : (k == 2 ? 2 : (k == 3 ? 1 : 0));
          for (int d = 0; d < nd; d++) { mbar_wait_u(bars + BAR_WEMPTY + 8 * slot, (eph >> slot) & 1); slot = (slot + 1) & (NW - 1); }
          if (k == 0) { TSTAMP(2, 11); poll_ge(cntA, (epoch + 1) * 128); fence_async_global(); TSTAMP(2, 4); }
        }
        rload(BAR_FULLB, 16384 + 14336, &P.wsp, 64 * k, t0, true, &P.zt, 64 * k, 112 * bj);
      }
      TSTAMP(2, 5);
      if (bj < 7) {
        mbar_wait_u(bars + BAR_OALL, 0);
        fence_async_global();
        TSTAMP(2, 6);
#pragma unroll 1
        for (int k = 0; k < 8; k++) {
          rwait();
          rload(BAR_FULLA, 24576, &P.old, 64 * k, t0, true, &P.wo, 64 * bj, 56 * k);
          tma_ld2(sbase + (rs == 0 ? NSLOT - 1 : rs - 1) * SLOT + 16384 + 4096, &P.wo, bars + BAR_FULLA + 8 * (rs == 0 ? NSLOT - 1 : rs - 1), 64 * bj, 56 * k + 28);
        }
        TSTAMP(2, 7);
        auto slc = [&](int k) { const int m = k >> 1; return m == 0 ? bj : (m - 1 < bj ? m - 1 : m); };
        const int rs0 = rs;
#pragma unroll 1
        for (int k = 0; k < 16; k++) {
          const int sl = slc(k);
          rwait();
          rload(BAR_FULLB, k < 2 ? 8192 : 24576, &P.uld, sl * 128 + (k & 1) * 64, t0, k >= NSLOT, &P.wout, 64 * bj, sl * 112 + (k & 1) * 64);
          if (k == NSLOT - 1) {
            TSTAMP(2, 8);
            mbar_wait_u(bars + BAR_UALL, 0);
            fence_async_global();
            TSTAMP(2, 9);
#pragma unroll 1
            for (int m = 2; m < NSLOT; m++) {
              const int r = (rs0 + m) % NSLOT;
              tma_ld2(sbase + r * SLOT, &P.uld, bars + BAR_FULLB + 8 * r, slc(m) * 128 + (m & 1) * 64, t0);
            }
          }
        }
        TSTAMP(2, 10);
      }
    } else if (warp == 17) {
#pragma unroll 1
      for (int w = 0; w < 2; w++) {
        mbar_wait_u(bars + BAR_ZRDY + 8 * w, 0);
        tma_st2(&P.zt, sc + SC_ZSTG + w * 14336, t0 + 64 * w, 112 * bj);
      }
      bulk_commit();
      TSTAMP(1, 12);
      bulk_wait_read();
      TSTAMP(1, 13);
      mbar_arrive(bars + BAR_ZFREE);
      bulk_wait_all();
      red_release(syncJ + 0);
#pragma unroll 1
      for (int w = 0; w < 2; w++) {
        mbar_wait_u(bars + BAR_U0RDY + 8 * w, 0);
        tma_st2(&P.ust, sbase + OFF_SPARE + w * 8192, 128 * bj, t0 + 64 * w);
      }
#pragma unroll 1
      for (int w = 0; w < 2; w++) {
        mbar_wait_u(bars + BAR_URDY + 8 * w, 0);
        tma_st2(&P.ust, sc + SC_U1 + w * 8192, 128 * bj + 64, t0 + 64 * w);
      }
      bulk_commit();
      TSTAMP(2, 13);
      bulk_wait_all();
      TSTAMP(2, 14);
      red_release(syncI + 3);
      poll_ge(syncI + 3, (epoch + 1) * 8);
      TSTAMP(2, 15);
      mbar_arrive(bars + BAR_UALL);
    } else if (warp == 18) {
      const int cta = bi * 8 + bj;
      mbar_wait_u(bars + BAR_RELRDY, 0);
      TSTAMP(2, 28);
      bulk_st(reinterpret_cast<uint8_t*>(g_Wq) + cta * 7168, sc + SC_RELAY, 7168);
      bulk_commit();
      bulk_wait_all();
      red_release(g_sync + 25 * 32);
      TSTAMP(2, 29);
      mbar_wait_u(bars + BAR_REL2RDY, 0);
      bulk_st(reinterpret_cast<uint8_t*>(g_Wz) + cta * 7168, sc + SC_RELAY + 7168, 7168);
      bulk_commit();
      bulk_wait_all();
      red_release(g_sync + 25 * 32 + 1);
      mbar_arrive(bars + BAR_RELDONE);
      mbar_wait_u(bars + BAR_GRDY, 0);
      bulk_st(g_KV + bj * 3584 + bi * 224, sc + SC_WPHI + 56 * 128, 896);
      bulk_st(g_gate + t0 + bj * 16, bars + OFF_GATE, 64);
      bulk_commit();
      bulk_wait_all();
      mbar_arrive(bars + BAR_ZEROD);
      red_release(syncJ + 2);
      poll_ge(syncJ + 2, (epoch + 1) * 16);
      mbar_wait_u(bars + BAR_KDRDY, 0);
      mbar_wait_u(bars + BAR_KDRDY + 8, 0);
      bulk_reduce_f32(g_KV + bj * 3584, sc + SC_KVS, 14336);
      TSTAMP(2, 20);
      bulk_commit();
      bulk_wait_all();
      red_release(syncJ + 1);
      TSTAMP(2, 21);
      poll_ge(syncJ + 1, (epoch + 1) * 16);
      TSTAMP(2, 22);
      fence_async_global();
      mbar_expect_tx(bars + BAR_KVF, 14336);
      bulk_ld(sc + SC_KVF, g_KV + bj * 3584, 14336, bars + BAR_KVF);
    } else {
#pragma unroll 1
      for (int w = 0; w < 2; w++) {
        mbar_wait_u(bars + BAR_ORDY + 8 * w, 0);
        tma_st2(&P.ost, sc + SC_OSTG + w * 8192, 64 * bj, t0 + 64 * w);
      }
      bulk_commit();
      bulk_wait_all();
      red_release(syncI + 2);
      TSTAMP(2, 23);
      poll_ge(syncI + 2, (epoch + 1) * 8);
      TSTAMP(2, 24);
      mbar_arrive(bars + BAR_OALL);
    }
  } else if (warp < 8) {
    bar_sync(8, NTHREADS);
    if (threadIdx.x == 0) TSTAMP(0, 18);
    asm volatile("setmaxnreg.inc.sync.aligned.u32 112;");
    if (threadIdx.x == 0) TSTAMP(0, 19);
    const int w = warp >> 2, ww = warp & 3, q = lane & 3;
    const int r0 = 64 * w + 16 * ww + (lane >> 2);
    unsigned epoch;
    uint2* strec = g_stats + bi * 1024 + r0;
    float acc[56];
    consume1<0, 0, true>(acc, sbase, w, lane, [&](auto si) {
      if (decltype(si)::value == 0) {
        epoch = ld_epoch(syncI + 8 + bj);
        if (q == 0) {
          st_relaxed2(strec + 128 * bj, make_uint2(0, 0));
          st_relaxed2(strec + 128 * bj + 8, make_uint2(0, 0));
        }
      }
    } TP(0));
    reg_fence<56>(acc);
    if (threadIdx.x == 0) TSTAMP(0, 0);
    {
      float s0 = 0.f, s1 = 0.f;
#pragma unroll
      for (int b = 0; b < 14; b++) {
        acc[4 * b] = gelu2_f(acc[4 * b]); acc[4 * b + 1] = gelu2_f(acc[4 * b + 1]);
        acc[4 * b + 2] = gelu2_f(acc[4 * b + 2]); acc[4 * b + 3] = gelu2_f(acc[4 * b + 3]);
        s0 += acc[4 * b] + acc[4 * b + 1];
        s1 += acc[4 * b + 2] + acc[4 * b + 3];
      }
      const float m0 = qsum(s0) * (1.f / 112.f), m1 = qsum(s1) * (1.f / 112.f);
      float v0 = 0.f, v1 = 0.f;
#pragma unroll
      for (int b = 0; b < 14; b++) {
        float d0 = acc[4 * b] - m0, d1 = acc[4 * b + 1] - m0, d2 = acc[4 * b + 2] - m1, d3 = acc[4 * b + 3] - m1;
        v0 = fmaf(d0, d0, v0); v0 = fmaf(d1, d1, v0);
        v1 = fmaf(d2, d2, v1); v1 = fmaf(d3, d3, v1);
      }
      v0 = qsum(v0); v1 = qsum(v1);
      if (q == 0) {
        const uint32_t tag = 1 + epoch % 3;
        st_relaxed2(strec + 128 * bj, make_uint2(__float_as_uint(m0), (__float_as_uint(v0) & ~3u) | tag));
        st_relaxed2(strec + 128 * bj + 8, make_uint2(__float_as_uint(m1), (__float_as_uint(v1) & ~3u) | tag));
      }
    }
    if (threadIdx.x == 0) TSTAMP(0, 1);
    {
      uint2 ra, rb, rc, rd;
      {
        const uint32_t tag = 1 + epoch % 3;
        uint32_t it = 0;
        while (true) {
          ra = ld_relaxed2(strec + 256 * q); rb = ld_relaxed2(strec + 256 * q + 128);
          rc = ld_relaxed2(strec + 256 * q + 8); rd = ld_relaxed2(strec + 256 * q + 128 + 8);
          const bool ok = (ra.y & 3u) == tag && (rb.y & 3u) == tag && (rc.y & 3u) == tag && (rd.y & 3u) == tag;
          if (__all_sync(~0u, ok) || ++it > (1u << 20)) break;
        }
      }
      if (threadIdx.x == 0) TSTAMP(0, 2);
      const float4 a = make_float4(__uint_as_float(ra.x), __uint_as_float(ra.y & ~3u), __uint_as_float(rb.x), __uint_as_float(rb.y & ~3u));
      const float4 c = make_float4(__uint_as_float(rc.x), __uint_as_float(rc.y & ~3u), __uint_as_float(rd.x), __uint_as_float(rd.y & ~3u));
      const float m0 = qsum(a.x + a.z) * 0.125f, m1 = qsum(c.x + c.z) * 0.125f;
      const float e0 = a.x - m0, e1 = a.z - m0, e2 = c.x - m1, e3 = c.z - m1;
      const float v0 = qsum(a.y + a.w + 112.f * (e0 * e0 + e1 * e1)) * (1.f / 896.f);
      const float v1 = qsum(c.y + c.w + 112.f * (e2 * e2 + e3 * e3)) * (1.f / 896.f);
      const float rs0 = rsqrtf(v0 + 4e-5f), rs1 = rsqrtf(v1 + 4e-5f);
      const float o0 = -m0 * rs0, o1 = -m1 * rs1;
      const uint32_t stg = sc + SC_ZSTG + w * 14336;
      mbar_wait(bars + BAR_RELDONE, 0);
      const int m = lane >> 3, rr = lane & 7;
      const uint32_t cofs = (uint32_t)(((2 * ww + (m & 1)) ^ rr) << 4);
#pragma unroll
      for (int b = 0; b < 14; b += 2) {
        uint32_t p0 = pack2(fmaf(acc[4 * b], rs0, o0), fmaf(acc[4 * b + 1], rs0, o0));
        uint32_t p1 = pack2(fmaf(acc[4 * b + 2], rs1, o1), fmaf(acc[4 * b + 3], rs1, o1));
        uint32_t p2 = pack2(fmaf(acc[4 * b + 4], rs0, o0), fmaf(acc[4 * b + 5], rs0, o0));
        uint32_t p3 = pack2(fmaf(acc[4 * b + 6], rs1, o1), fmaf(acc[4 * b + 7], rs1, o1));
        stsm4t(stg + (8 * (b + (m >> 1)) + rr) * 128 + cofs, p0, p1, p2, p3);
      }
      fence_async_smem();
      __syncwarp();
      if (lane == 0) mbar_arrive(bars + BAR_ZRDY + 8 * w);
    }
    if (threadIdx.x == 0) TSTAMP(0, 3);
    consume1<0, 17, false>(acc, sbase, w, lane, NoHook() TP(21));
    reg_fence<56>(acc);
    if (threadIdx.x == 0) TSTAMP(0, 4);
    uint32_t z1[28];
#pragma unroll
    for (int b = 0; b < 14; b++) {
      z1[2 * b] = pack2(acc[4 * b], acc[4 * b + 1]);
      z1[2 * b + 1] = pack2(acc[4 * b + 2], acc[4 * b + 3]);
    }
    const float bs0 = 0.5f * __bfloat162float(P.bsp[bi * 128 + r0]), bs1 = 0.5f * __bfloat162float(P.bsp[bi * 128 + r0 + 8]);
    if (threadIdx.x == 0) TSTAMP(0, 5);
    consume2<0>(acc, sbase, w, lane, [&](int it) {
      switch (it) {
        case 0: for_range<0, 5>([&](auto c) { z1[decltype(c)::value] = gelu2_pack(z1[decltype(c)::value]); }); break;
        case 1: for_range<5, 10>([&](auto c) { z1[decltype(c)::value] = gelu2_pack(z1[decltype(c)::value]); }); break;
        case 2: for_range<10, 15>([&](auto c) { z1[decltype(c)::value] = gelu2_pack(z1[decltype(c)::value]); }); break;
        case 3: for_range<15, 20>([&](auto c) { z1[decltype(c)::value] = gelu2_pack(z1[decltype(c)::value]); }); break;
        case 4: for_range<20, 24>([&](auto c) { z1[decltype(c)::value] = gelu2_pack(z1[decltype(c)::value]); }); break;
        default: for_range<24, 28>([&](auto c) { z1[decltype(c)::value] = gelu2_pack(z1[decltype(c)::value]); }); break;
      }
    } TP(28));
    reg_fence<56>(acc);
    if (threadIdx.x == 0) TSTAMP(0, 6);
    {
      auto ublk = [&](int b, uint32_t* u) {
        const float a0 = __uint_as_float(z1[2 * b] << 16), a1 = __uint_as_float(z1[2 * b] & 0xffff0000u);
        const float a2 = __uint_as_float(z1[2 * b + 1] << 16), a3 = __uint_as_float(z1[2 * b + 1] & 0xffff0000u);
        u[0] = pack2(a0 * fmaf(acc[4 * b], 0.5f, bs0), a1 * fmaf(acc[4 * b + 1], 0.5f, bs0));
        u[1] = pack2(a2 * fmaf(acc[4 * b + 2], 0.5f, bs1), a3 * fmaf(acc[4 * b + 3], 0.5f, bs1));
      };
      uint32_t u[16];
#pragma unroll
      for (int b = 0; b < 8; b++) ublk(b, u + 2 * b);
      store_frag<8>(sbase + OFF_SPARE, 64 * w + 16 * ww, u, lane);
      fence_async_smem();
      __syncwarp();
      if (lane == 0) mbar_arrive(bars + BAR_U0RDY + 8 * w);
      if (threadIdx.x == 0) TSTAMP(0, 21);
#pragma unroll
      for (int b = 8; b < 14; b++) ublk(b, u + 2 * (b - 8));
      mbar_wait(bars + BAR_SCFREE, 0);
      store_frag<6>(sc + SC_U1, 64 * w + 16 * ww, u, lane);
      fence_async_smem();
      __syncwarp();
      if (lane == 0) mbar_arrive(bars + BAR_URDY + 8 * w);
    }
    if (threadIdx.x == 0) TSTAMP(0, 7);
    if (bj < 7) {
      float acc[32];
      bar_sync(1 + w, 128);
      consume2<2>(acc, sbase, w, lane, NoHook() TP(68));
      reg_fence<32>(acc);
      if (threadIdx.x == 0) TSTAMP(0, 8);
      bar_sync(6, 512);
      const float* ap = reinterpret_cast<const float*>(sgen + OFF_SC + SC_APART) + (threadIdx.x & 255);
      const float* gs = reinterpret_cast<const float*>(sgen + OFF_BAR + OFF_GATE);
      const float g0 = 1.f - gs[r0], g1 = 1.f - gs[r0 + 8];
      uint32_t o[16];
#pragma unroll
      for (int b = 0; b < 8; b++) {
        o[2 * b] = pack2(fmaf(acc[4 * b], g0, ap[(4 * b) * 256]), fmaf(acc[4 * b + 1], g0, ap[(4 * b + 1) * 256]));
        o[2 * b + 1] = pack2(fmaf(acc[4 * b + 2], g1, ap[(4 * b + 2) * 256]), fmaf(acc[4 * b + 3], g1, ap[(4 * b + 3) * 256]));
      }
      store_frag<8>(sbase + OFF_SPARE, 64 * w + 16 * ww, o, lane);
      fence_async_smem();
      bar_sync(1 + w, 128);
      if (ww == 0 && lane == 0) {
        tma_st2(&P.out, sbase + OFF_SPARE + w * 8192, 64 * bj, bi * 128 + 64 * w);
        bulk_commit();
        bulk_wait_read();
      }
    }
    if (threadIdx.x == 0) syncI[8 + bj] = epoch + 1;
    if (threadIdx.x == 0) TSTAMP(0, 9);
  } else {
    bar_sync(8, NTHREADS);
    asm volatile("setmaxnreg.inc.sync.aligned.u32 112;");
    const int tid = threadIdx.x - 256;
    const int w = (warp >> 2) & 1, ww = warp & 3, q = lane & 3;
    const int wrow = 64 * w + 16 * ww;
    const int r0 = wrow + (lane >> 2);
    const int cta = bi * 8 + bj;
    {
      uint4 rq[2];
#pragma unroll
      for (int m = 0; m < 2; m++) {
        const int t = tid + 256 * m, r = 56 * cta + (t >> 3), ch = t & 7, sg = r / DM, k = r - sg * DM;
        const int sh = sg >= 8 ? (ch >> 2) : 0, g0 = 2 * ch - sh, g1 = g0 + 1;
        const bool v0 = t < 448 && (sg >= 8 || ch < 7), v1 = t < 448 && (sg >= 8 ? (ch & 3) != 3 : ch < 7);
        const __nv_bfloat16* src = P.wqkv_ptr + k * 1344 + (8 + sg) * 56;
        uint2 lo = make_uint2(0, 0), hi = make_uint2(0, 0);
        if (v0) lo = __ldg(reinterpret_cast<const uint2*>(src + 4 * g0));
        if (v1) hi = __ldg(reinterpret_cast<const uint2*>(src + 4 * g1));
        rq[m] = make_uint4(lo.x, lo.y, hi.x, hi.y);
      }
      const __nv_bfloat16* wsrc = P.wphi + bj * 2 * 784;
      uint32_t wv[4];
#pragma unroll
      for (int m = 0; m < 4; m++) { const int e = tid + 256 * m; wv[m] = e < 784 ? __ldg(reinterpret_cast<const uint32_t*>(wsrc) + e) : 0u; }
      uint4* wp = reinterpret_cast<uint4*>(sgen + OFF_SC + SC_WPHI);
      wp[tid] = make_uint4(0, 0, 0, 0);
      wp[tid + 256] = make_uint4(0, 0, 0, 0);
      uint4* rs = reinterpret_cast<uint4*>(sgen + OFF_SC + SC_RELAY);
#pragma unroll
      for (int m = 0; m < 2; m++) { const int t = tid + 256 * m; if (t < 448) rs[t] = rq[m]; }
      fence_async_smem();
      __syncwarp();
      if (lane == 0) mbar_arrive(bars + BAR_RELRDY);
      {
        uint4 rz[2];
#pragma unroll
        for (int m = 0; m < 2; m++) {
          const int t = tid + 256 * m, r = 28 * cta + (t >> 4), ch = t & 15, seg = r / DM, k = r - seg * DM;
          rz[m] = make_uint4(0, 0, 0, 0);
          if (t < 448 && ch < 14) rz[m] = __ldg(reinterpret_cast<const uint4*>(P.win_ptr + k * 1792 + seg * 112 + ch * 8));
        }
#pragma unroll
        for (int m = 0; m < 2; m++) { const int t = tid + 256 * m; if (t < 448) rs[448 + t] = rz[m]; }
        fence_async_smem();
        __syncwarp();
        if (lane == 0) mbar_arrive(bars + BAR_REL2RDY);
      }
      bar_sync(5, 256);
      uint32_t* wt = reinterpret_cast<uint32_t*>(sgen + OFF_SC + SC_WPHI);
#pragma unroll
      for (int m = 0; m < 4; m++) {
        const int e = tid + 256 * m;
        if (e < 784) {
          const int h = e >= 392, rem = e - h * 392, d = rem / 14, f = 2 * (rem - d * 14);
          const int k = 28 * h + d, n = 28 * h + f;
          wt[k * 32 + ((((n >> 3) ^ (k & 7)) << 2) | ((n & 7) >> 1))] = wv[m];
        }
      }
      fence_async_smem();
      bar_sync(5, 256);
    }
    if (tid == 0) TSTAMP(1, 0);
    const uint64_t dWphi = desc_mn(sc + SC_WPHI);
    uint32_t qp[14];
    {
      float accq[28];
      consume_q(accq, sbase, w, lane TP(7));
      reg_fence<28>(accq);
      if (tid == 0) TSTAMP(1, 2);
#pragma unroll
      for (int i = 0; i < 14; i++) qp[i] = pack2(accq[2 * i], accq[2 * i + 1]);
      float pq[28];
      wg_fence();
#pragma unroll
      for (int k = 0; k < 3; k++) wgmma_rs_n56_t1(pq, qp[4 * k], qp[4 * k + 1], qp[4 * k + 2], qp[4 * k + 3], dWphi + 128 * k, k != 0);
      wgmma_rs_n56_t1(pq, qp[12], qp[13], 0u, 0u, dWphi + 128 * 3, 1);
      wg_commit();
      {
        const int gl = tid & 15, grow = bj * 16 + (tid >> 4);
        const uint8_t* xrow = sgen + OFF_X + grow * 128 + (((gl >> 1) ^ (grow & 7)) << 4) + (gl & 1) * 8;
        float gsum = 0.f;
#pragma unroll
        for (int m = 0; m < 7; m++) {
          const uint2 xv = *reinterpret_cast<const uint2*>(xrow + m * 16384);
          const uint2 gv = __ldg(reinterpret_cast<const uint2*>(P.gatew + 64 * m + 4 * gl));
          gsum = fmaf(__uint_as_float(xv.x << 16), __uint_as_float(gv.x << 16), gsum);
          gsum = fmaf(__uint_as_float(xv.x & 0xffff0000u), __uint_as_float(gv.x & 0xffff0000u), gsum);
          gsum = fmaf(__uint_as_float(xv.y << 16), __uint_as_float(gv.y << 16), gsum);
          gsum = fmaf(__uint_as_float(xv.y & 0xffff0000u), __uint_as_float(gv.y & 0xffff0000u), gsum);
        }
#pragma unroll
        for (int o = 8; o > 0; o >>= 1) gsum += __shfl_xor_sync(~0u, gsum, o);
        if (gl == 0) reinterpret_cast<float*>(sgen + OFF_BAR + OFF_GATE)[tid >> 4] = 1.f / (1.f + __expf(-gsum));
        fence_async_smem();
        __syncwarp();
        if (lane == 0) mbar_arrive(bars + BAR_GRDY);
      }
      wg_wait<0>();
      reg_fence<28>(pq);
#pragma unroll
      for (int i = 0; i < 14; i++) qp[i] = pack2(pq[2 * i], pq[2 * i + 1]);
    }
    {
      uint32_t kp[16], vp[16];
      {
        float acc[64];
        consume1<2, 11, false>(acc, sbase, w, lane, NoHook() TP(14));
        reg_fence<64>(acc);
        if (tid == 0) TSTAMP(1, 1);
#pragma unroll
        for (int b = 0; b < 8; b++) {
          vp[2 * b] = pack2(acc[32 + 4 * b], acc[32 + 4 * b + 1]);
          vp[2 * b + 1] = pack2(acc[32 + 4 * b + 2], acc[32 + 4 * b + 3]);
        }
        if (q == 2) vp[6] = vp[7] = vp[14] = vp[15] = 0x00003f80u;
#pragma unroll
        for (int i = 0; i < 16; i++) kp[i] = pack2(acc[2 * i], acc[2 * i + 1]);
      }
      const uint32_t tV = sc + 8192 + w * 16384, tP = tV + 8192, tM = sc + w * 40960;
      mbar_wait_u(bars + BAR_ZFREE, 0);
      store_frag<8>(tV, 16 * ww, vp, lane);
      float pk[28];
      wg_fence();
#pragma unroll
      for (int k = 0; k < 4; k++) wgmma_rs_n56_t1(pk, kp[4 * k], kp[4 * k + 1], kp[4 * k + 2], kp[4 * k + 3], dWphi + 128 * k, k != 0);
      wg_commit();
      wg_wait<0>();
      reg_fence<28>(pk);
      uint32_t f[28];
      feature_map(pk, f, q);
      if (tid == 0) TSTAMP(1, 3);
      mbar_wait_u(bars + BAR_ZEROD, 0);
      bar_sync(5, 256);
      store_frag<7>(tP, 16 * ww, f, lane);
      store_frag<7>(tM, 16 * ww, f + 14, lane);
      fence_async_smem();
      bar_sync(5, 256);
      float kv[32];
      {
        const uint64_t dA0 = desc_mn(w ? sc : sc + 16384), dA1 = desc_mn(w ? sc + 40960 : sc + 32768);
        const uint64_t dB0 = desc_mn(sc + 8192), dB1 = desc_mn(sc + 24576);
        wg_fence();
#pragma unroll
        for (int k = 0; k < 4; k++) wgmma_ss_n64_t11(kv, dA0 + 128 * k, dB0 + 128 * k, k != 0);
#pragma unroll
        for (int k = 0; k < 4; k++) wgmma_ss_n64_t11(kv, dA1 + 128 * k, dB1 + 128 * k, 1);
        wg_commit();
        wg_wait<0>();
        reg_fence<32>(kv);
      }
      bar_sync(5, 256);
      {
        const int sw = lane & 28;
#pragma unroll
        for (int r = 0; r < 2; r++) {
          const int c = 16 * ww + (lane >> 2) + 8 * r;
          if (c < 56) {
            const bool h1 = c >= 28;
            float* d0 = reinterpret_cast<float*>(sgen + OFF_SC + SC_KVS) + (56 * w + c) * 32;
#pragma unroll
            for (int b = 0; b < 4; b++)
              *reinterpret_cast<float2*>(d0 + ((8 * b + 2 * q) ^ sw)) =
                  h1 ? make_float2(kv[16 + 4 * b + 2 * r], kv[17 + 4 * b + 2 * r]) : make_float2(kv[4 * b + 2 * r], kv[4 * b + 2 * r + 1]);
          }
        }
      }
      fence_async_smem();
      __syncwarp();
      if (lane == 0) mbar_arrive(bars + BAR_KDRDY + 8 * w);
    }
    if (tid == 0) TSTAMP(1, 4);
    uint32_t fq[28];
    {
      float pq[28];
#pragma unroll
      for (int i = 0; i < 14; i++) { pq[2 * i] = __uint_as_float(qp[i] << 16); pq[2 * i + 1] = __uint_as_float(qp[i] & 0xffff0000u); }
      feature_map(pq, fq, q);
    }
    if (tid == 0) TSTAMP(1, 6);
    if (tid < 49) prefetch_l2(reinterpret_cast<const char*>(P.wout_ptr) + cta * 6272 + tid * 128);
    else if (tid >= 64 && tid < 64 + 25) prefetch_l2(reinterpret_cast<const char*>(P.wo_ptr) + cta * 3136 + (tid - 64) * 128);
    mbar_wait_u(bars + BAR_KVF, 0);
    if (lane == 0) mbar_arrive(bars + BAR_SCFREE);
    if (tid == 0) TSTAMP(1, 7);
    {
      const float* kf = reinterpret_cast<const float*>(sgen + OFF_SC + SC_KVF);
      const int ch = tid & 7, k0 = tid >> 3, sw = (k0 & 7) << 2, d0 = 8 * (ch & 3);
#pragma unroll
      for (int m = 0; m < 4; m++) {
        const int k = k0 + 32 * m;
        if (k < 112) {
          const int hc = (k >= 56 ? k - 56 : k) >= 28;
          uint4 v = make_uint4(0, 0, 0, 0);
          if ((ch >> 2) == hc) {
            const float4 a = *reinterpret_cast<const float4*>(kf + k * 32 + (d0 ^ sw)), b = *reinterpret_cast<const float4*>(kf + k * 32 + ((d0 + 4) ^ sw));
            v = make_uint4(pack2(a.x, a.y), pack2(a.z, a.w), pack2(b.x, b.y), pack2(b.z, b.w));
          }
          *reinterpret_cast<uint4*>(sgen + OFF_SC + SC_KVB + k * 128 + ((ch ^ (k & 7)) << 4)) = v;
        }
      }
      fence_async_smem();
      bar_sync(5, 256);
      if (tid == 0) TSTAMP(1, 11);
      float o[32];
      const uint64_t dB = desc_mn(sc + SC_KVB);
      wg_fence();
#pragma unroll
      for (int k = 0; k < 7; k++) wgmma_rs_n64_t1(o, fq[4 * k], fq[4 * k + 1], fq[4 * k + 2], fq[4 * k + 3], dB + 128 * k, k != 0);
      wg_commit();
      wg_wait<0>();
      reg_fence<32>(o);
      uint32_t op[16];
#pragma unroll
      for (int r = 0; r < 2; r++) {
        const float d0 = __shfl_sync(~0u, o[12 + 2 * r], (lane & ~3) | 2), d1 = __shfl_sync(~0u, o[28 + 2 * r], (lane & ~3) | 2);
        const float i0 = rcpf(d0 + 1e-6f), i1 = rcpf(d1 + 1e-6f);
#pragma unroll
        for (int b = 0; b < 8; b++) {
          const float iv = b < 4 ? i0 : i1;
          const uint32_t v = pack2(o[4 * b + 2 * r] * iv, o[4 * b + 2 * r + 1] * iv);
          op[2 * b + r] = ((b & 3) == 3 && q >= 2) ? 0u : v;
        }
      }
      store_frag<8>(sc + SC_OSTG, wrow, op, lane);
      fence_async_smem();
      __syncwarp();
      if (lane == 0) mbar_arrive(bars + BAR_ORDY + 8 * w);
    }
    if (tid == 0) TSTAMP(1, 8);
    if (bj < 7) {
      float acc[32];
      mbar_wait_u(bars + BAR_URDY, 0);
      mbar_wait_u(bars + BAR_URDY + 8, 0);
      consume2<1>(acc, sbase, w, lane, NoHook() TP(60));
      reg_fence<32>(acc);
      if (tid == 0) TSTAMP(1, 9);
      mbar_wait(bars + BAR_OALL, 0);
      const float g0 = __ldcg(g_gate + bi * 128 + r0), g1 = __ldcg(g_gate + bi * 128 + r0 + 8);
      bar_sync(5, 256);
      float* ap = reinterpret_cast<float*>(sgen + OFF_SC + SC_APART) + tid;
#pragma unroll
      for (int b = 0; b < 8; b++) {
        ap[(4 * b) * 256] = acc[4 * b] * g0;
        ap[(4 * b + 1) * 256] = acc[4 * b + 1] * g0;
        ap[(4 * b + 2) * 256] = acc[4 * b + 2] * g1;
        ap[(4 * b + 3) * 256] = acc[4 * b + 3] * g1;
      }
      if (q == 0) {
        float* gs = reinterpret_cast<float*>(sgen + OFF_BAR + OFF_GATE);
        gs[r0] = g0; gs[r0 + 8] = g1;
      }
      bar_arrive(6, 512);
    }
    if (tid == 0) TSTAMP(1, 10);
  }
}

typedef CUresult (*EncodeFn)(CUtensorMap*, CUtensorMapDataType, cuuint32_t, void*, const cuuint64_t*, const cuuint64_t*, const cuuint32_t*,
                             const cuuint32_t*, CUtensorMapInterleave, CUtensorMapSwizzle, CUtensorMapL2promotion, CUtensorMapFloatOOBfill);

static void map2(EncodeFn fn, CUtensorMap* m, const void* p, uint64_t rows, uint64_t cols, uint32_t brows, uint32_t bcols,
                 CUtensorMapL2promotion promo = CU_TENSOR_MAP_L2_PROMOTION_L2_128B) {
  cuuint64_t gd[2] = {cols, rows};
  cuuint64_t gs[1] = {cols * 2};
  cuuint32_t bd[2] = {bcols, brows};
  cuuint32_t es[2] = {1, 1};
  fn(m, CU_TENSOR_MAP_DATA_TYPE_BFLOAT16, 2, const_cast<void*>(p), gd, gs, bd, es, CU_TENSOR_MAP_INTERLEAVE_NONE, CU_TENSOR_MAP_SWIZZLE_128B,
     promo, CU_TENSOR_MAP_FLOAT_OOB_FILL_NONE);
}
static void map3(EncodeFn fn, CUtensorMap* m, const void* p, uint64_t rows, uint64_t nseg, uint64_t seg, uint32_t brows) {
  cuuint64_t gd[3] = {seg, nseg, rows};
  cuuint64_t gs[2] = {seg * 2, nseg * seg * 2};
  cuuint32_t bd[3] = {64, 1, brows};
  cuuint32_t es[3] = {1, 1, 1};
  fn(m, CU_TENSOR_MAP_DATA_TYPE_BFLOAT16, 3, const_cast<void*>(p), gd, gs, bd, es, CU_TENSOR_MAP_INTERLEAVE_NONE, CU_TENSOR_MAP_SWIZZLE_128B,
     CU_TENSOR_MAP_L2_PROMOTION_L2_128B, CU_TENSOR_MAP_FLOAT_OOB_FILL_NONE);
}

}

extern "C" void kernel_launch(void* const* d_in, const int* in_sizes, int n_in, void* d_out, int out_size) {
  using namespace hk;
  (void)in_sizes; (void)n_in; (void)out_size;
  static EncodeFn fn = nullptr;
  static void *pZT, *pU, *pO, *pWq, *pWz;
  if (!fn) {
    void* p = nullptr;
    cudaDriverEntryPointQueryResult qr;
    cudaGetDriverEntryPoint("cuTensorMapEncodeTiled", &p, cudaEnableDefault, &qr);
    fn = (EncodeFn)p;
    cudaGetSymbolAddress(&pZT, g_ZT);
    cudaGetSymbolAddress(&pU, g_U);
    cudaGetSymbolAddress(&pO, g_O);
    cudaGetSymbolAddress(&pWq, g_Wq);
    cudaGetSymbolAddress(&pWz, g_Wz);
    cudaFuncSetAttribute(fused_kernel, cudaFuncAttributeMaxDynamicSharedMemorySize, SMEM_BYTES);
  }
  Params P = {};
  map2(fn, &P.x, d_in[0], SEQ, DM, 128, 64);
  map2(fn, &P.win, d_in[5], DM, 2 * FH, 64, 64);
  map3(fn, &P.wq3, d_in[1], DM, 24, 56, 64);
  map2(fn, &P.wq, pWq, 16 * DM, 64, 64, 64);
  map2(fn, &P.wz, pWz, 8 * DM, 128, 64, 64);
  map2(fn, &P.ost, pO, SEQ, 512, 64, 64);
  map2(fn, &P.wsp, d_in[6], SEQ, SEQ, 128, 64);
  map2(fn, &P.zt, pZT, FH, SEQ, 112, 64);
  map2(fn, &P.ust, pU, SEQ, 1024, 64, 64);
  map2(fn, &P.uld, pU, SEQ, 1024, 128, 64);
  map2(fn, &P.old, pO, SEQ, 512, 128, 64);
  map2(fn, &P.wout, d_in[8], FH, DM, 64, 64);
  map2(fn, &P.wo, d_in[3], DM, DM, 32, 64);
  map2(fn, &P.out, d_out, SEQ, DM, 64, 64);
  P.x_ptr = (const __nv_bfloat16*)d_in[0];
  P.wqkv_ptr = (const __nv_bfloat16*)d_in[1];
  P.wphi = (const __nv_bfloat16*)d_in[2];
  P.wo_ptr = (const __nv_bfloat16*)d_in[3];
  P.win_ptr = (const __nv_bfloat16*)d_in[5];
  P.wsp_ptr = (const __nv_bfloat16*)d_in[6];
  P.bsp = (const __nv_bfloat16*)d_in[7];
  P.wout_ptr = (const __nv_bfloat16*)d_in[8];
  P.gatew = (const __nv_bfloat16*)d_in[9];
  fused_kernel<<<128, NTHREADS, SMEM_BYTES, cudaStreamPerThread>>>(P);
}
```
